```python
import torch

def _softmax(x, axis=-1):
    return torch.softmax(x, dim=axis)
def _gelu(x):
    return torch.nn.functional.gelu(x, approximate="tanh")
def _silu(x):
    return torch.nn.functional.silu(x)
def _sigmoid(x):
    return torch.sigmoid(x)
def _layernorm(x, axis=-1, eps=1e-5):
    m = x.mean(dim=axis, keepdim=True)
    v = x.var(dim=axis, keepdim=True, unbiased=False)
    return (x - m) / torch.sqrt(v + eps)
def _scatter_add(tgt, idx, src, axis=0):
    return tgt.clone().index_add_(axis, idx, src)
def _segment_sum(src, seg, n):
    out = torch.zeros((n,) + src.shape[1:], dtype=src.dtype)
    return out.index_add_(0, seg, src)
def _pad(x, pw):
    flat = tuple(v for pair in reversed(pw) for v in pair)
    return torch.nn.functional.pad(x, flat)

kernel_name = 'parallel_sum__gqa_block_cached__swiglu_ffn__decode'

def setup_inputs():

    _w = (lambda a: (lambda t: t.to(torch.bfloat16) if t.is_floating_point() else t)(torch.as_tensor(a)))
    def _A_setup():
        B, Sq, D = 1, 1, 576
        Hq, Hkv, Sk, Dh = 32, 16, 16384, 128
        assert Hq % Hkv == 0, (Hq, Hkv)
        return {
            "x": _w((lambda *s: torch.randn(*s, dtype=torch.bfloat16) * 0.05)(B, Sq, D)),
            "k_cache": _w((lambda *s: torch.randn(*s, dtype=torch.bfloat16) * 3.2)(B, Hkv, Sk, Dh)),
            "v_cache": _w((lambda *s: torch.randn(*s, dtype=torch.bfloat16) * 1.6)(B, Hkv, Sk, Dh)),
            "wq": _w((lambda *s: torch.randn(*s, dtype=torch.bfloat16) * 3.2)(D, Hq * Dh) * (D ** -0.5)),
            "wo": _w((lambda *s: torch.randn(*s, dtype=torch.bfloat16) * 1.6)(Hq * Dh, D) * ((Hq * Dh) ** -0.5)),
        }
    _A_in = _A_setup()

    def _B_setup():
        B, S, D, F = 1, 1, 576, 4608
        return {
            "x": _w((lambda *s: torch.randn(*s, dtype=torch.bfloat16) * 0.05)(B, S, D)),
            "w_gate": _w((lambda *s: torch.randn(*s, dtype=torch.bfloat16) * 0.05)(D, F)),
            "w_up": _w((lambda *s: torch.randn(*s, dtype=torch.bfloat16) * 0.05)(D, F)),
            "w_down": _w((lambda *s: torch.randn(*s, dtype=torch.bfloat16) * 0.05)(F, D)),
        }
    _B_in = _B_setup()

    return {
        "A_x": _A_in["x"],
        "A_k_cache": _A_in["k_cache"],
        "A_v_cache": _A_in["v_cache"],
        "A_wq": _A_in["wq"],
        "A_wo": _A_in["wo"],
        "B_x": _B_in["x"],
        "B_w_gate": _B_in["w_gate"],
        "B_w_up": _B_in["w_up"],
        "B_w_down": _B_in["w_down"],
    }

def reference(A_x, A_k_cache, A_v_cache, A_wq, A_wo, B_x, B_w_gate, B_w_up, B_w_down):
    def _A_ref(x, k_cache, v_cache, wq, wo):
        B, Sq, D = x.shape
        Hq, Dh = 32, 128
        Hkv = k_cache.shape[1]
        rep = Hq // Hkv
        q = (lambda x, *d: x.permute(*d))((x @ wq).reshape(B, Sq, Hq, Dh), 0, 2, 1, 3)
        k = (lambda x, n, axis: torch.repeat_interleave(x, n, dim=axis))(k_cache, rep, axis=1)
        v = (lambda x, n, axis: torch.repeat_interleave(x, n, dim=axis))(v_cache, rep, axis=1)
        scores = torch.einsum("bhqd,bhkd->bhqk", q, k) * (Dh ** -0.5)
        p = _softmax(scores, axis=-1)
        o = torch.einsum("bhqk,bhkd->bhqd", p, v)
        return (lambda x, *d: x.permute(*d))(o, 0, 2, 1, 3).reshape(B, Sq, Hq * Dh) @ wo

    def _B_ref(x, w_gate, w_up, w_down):
        g = _silu(x @ w_gate)
        u = x @ w_up
        return (g * u) @ w_down

    x = A_x
    xn = _layernorm(x, axis=-1)
    return x + _A_ref(xn, A_k_cache, A_v_cache, A_wq, A_wo) + _B_ref(xn, B_w_gate, B_w_up, B_w_down)
```

```cpp
#include <cuda_runtime.h>
#include <cuda.h>
#include <cuda_bf16.h>
#include <stdint.h>

namespace {

constexpr int D_MODEL = 576;
constexpr int NQ = 4096;
constexpr int FF = 4608;

constexpr int NCTA = 132;
constexpr int ATT_CTAS = 128;
constexpr int NTHREADS = 352;

#define ATT_WARPS 4
#define DEPTH 4
constexpr int AW = ATT_WARPS;
constexpr int TP = 64;
constexpr int NT = 2048 / TP;
constexpr int SLOT = TP * 256;
constexpr int NSLOT = 13;
constexpr int WSL = 32 * D_MODEL * 2;
#define GU_MID 4
#define GU_AT 8
#define GU_EVERY 4
constexpr int IT_KV = 3, IT_FFN = IT_KV + 2 * NT, IT_END = IT_FFN + 12;
__host__ __device__ constexpr int item_of_tile(int n) {
    int e = n < GU_AT ? 0 : (n - GU_AT) / GU_EVERY + 1;
    return IT_KV + 2 * n + (e < GU_MID ? e : GU_MID);
}
__host__ __device__ constexpr int item_of_w(int j) { return j < GU_MID ? IT_KV + 2 * (GU_AT + j * GU_EVERY) + j : IT_FFN + j; }
static_assert(GU_MID == 0 || GU_AT + (GU_MID - 1) * GU_EVERY < NT, "");

constexpr int OFF_RED = NSLOT * SLOT;
constexpr int OFF_XN = OFF_RED + 3 * 8 * 32 * 4;
constexpr int OFF_Q = OFF_XN + D_MODEL * 4;
constexpr int OFF_H = OFF_Q + 512;
constexpr int OFF_O = OFF_H + 128;
constexpr int OFF_OWN = OFF_O + 128;
constexpr int OFF_MO = OFF_OWN + 144;
constexpr int OFF_ML = OFF_MO + AW * 256 * 4;
constexpr int OFF_BAR = OFF_ML + AW * 16;
constexpr int NBAR = 2 * NSLOT;
constexpr int OFF_PACE = OFF_BAR + NBAR * 8;
constexpr int SMEM_BYTES = OFF_PACE + 16 + 1024;

static_assert(SMEM_BYTES <= 232448, "smem");

#define POLL_NS 100
#define DMIN 3
#define DMAX 6
#define PACE_TH 64
#define PACE_STEP 2
#define PACE_I0 12
#define PACE_N ((IT_FFN - PACE_I0) / PACE_STEP)
#define TDEPTH 0
#define PACE 1
#define NCOPY_ 4
constexpr int NCOPY = NCOPY_;
static_assert(NCTA % NCOPY == 0, "");
constexpr int SPIN_LIMIT = 1 << 22;
constexpr float LOG2E = 1.4426950408889634f;

__device__ unsigned g_epoch;
__device__ __align__(128) unsigned long long g_q[NQ];
__device__ __align__(128) unsigned long long g_po[ATT_CTAS][8][48];
__device__ __align__(128) unsigned g_prog[32];
__device__ __align__(128) float4 g_acc[NCOPY][288];
#define TR(i)
#define TRW(i)

__device__ __forceinline__ uint32_t smem_u32(const void* p) { return (uint32_t)__cvta_generic_to_shared(p); }
__device__ __forceinline__ void mbar_init(uint32_t bar, uint32_t cnt) {
    asm volatile("mbarrier.init.shared::cta.b64 [%0], %1;" ::"r"(bar), "r"(cnt) : "memory");
}
__device__ __forceinline__ void mbar_expect_tx(uint32_t bar, uint32_t bytes) {
    asm volatile("mbarrier.arrive.expect_tx.shared::cta.b64 _, [%0], %1;" ::"r"(bar), "r"(bytes) : "memory");
}
__device__ __forceinline__ void mbar_arrive(uint32_t bar) {
    asm volatile("mbarrier.arrive.shared::cta.b64 _, [%0];" ::"r"(bar) : "memory");
}
__device__ __forceinline__ void mbar_arrive4(uint32_t bar) {
    asm volatile("mbarrier.arrive.shared::cta.b64 _, [%0], 4;" ::"r"(bar) : "memory");
}
__device__ __forceinline__ void mbar_wait(uint32_t bar, uint32_t parity) {
    for (int it = 0; it < SPIN_LIMIT; it++) {
        uint32_t ok;
        asm volatile(
            "{\n.reg .pred p;\n"
            "mbarrier.try_wait.parity.shared::cta.b64 p, [%1], %2;\n"
            "selp.u32 %0, 1, 0, p;\n}\n"
            : "=r"(ok) : "r"(bar), "r"(parity) : "memory");
        if (ok) break;
    }
}
__device__ __forceinline__ bool mbar_try(uint32_t bar, uint32_t parity) {
    uint32_t ok;
    asm volatile(
        "{\n.reg .pred p;\n"
        "mbarrier.try_wait.parity.shared::cta.b64 p, [%1], %2, %3;\n"
        "selp.u32 %0, 1, 0, p;\n}\n"
        : "=r"(ok) : "r"(bar), "r"(parity), "r"(200) : "memory");
    return ok;
}
__device__ __forceinline__ void bulk_g2s(uint32_t dst, const void* src, uint32_t bytes, uint32_t bar, uint64_t pol) {
    asm volatile(
        "cp.async.bulk.shared::cluster.global.mbarrier::complete_tx::bytes.L2::cache_hint [%0], [%1], %2, [%3], %4;"
        ::"r"(dst), "l"(src), "r"(bytes), "r"(bar), "l"(pol) : "memory");
}
__device__ __forceinline__ void tma2d(uint32_t dst, const CUtensorMap* map, int c0, int c1, uint32_t bar, uint64_t pol) {
    asm volatile(
        "cp.async.bulk.tensor.2d.shared::cluster.global.mbarrier::complete_tx::bytes.L2::cache_hint "
        "[%0], [%1, {%3, %4}], [%2], %5;"
        ::"r"(dst), "l"(map), "r"(bar), "r"(c0), "r"(c1), "l"(pol) : "memory");
}
__device__ __forceinline__ uint4 lds128(uint32_t addr) {
    uint4 v;
    asm volatile("ld.shared.v4.u32 {%0,%1,%2,%3}, [%4];" : "=r"(v.x), "=r"(v.y), "=r"(v.z), "=r"(v.w) : "r"(addr) : "memory");
    return v;
}
__device__ __forceinline__ unsigned long long pack_pkt(float v, unsigned tag) {
    return (unsigned long long)__float_as_uint(v) | ((unsigned long long)tag << 32);
}
__device__ __forceinline__ void st_pkt(unsigned long long* p, unsigned long long v) {
    asm volatile("st.relaxed.gpu.global.b64 [%0], %1;" ::"l"(p), "l"(v) : "memory");
}
__device__ __forceinline__ void st_pkt2(unsigned long long* p, unsigned long long a, unsigned long long b) {
    asm volatile("st.relaxed.gpu.global.v2.b64 [%0], {%1, %2};" ::"l"(p), "l"(a), "l"(b) : "memory");
}
__device__ __forceinline__ unsigned long long ld_pkt(const unsigned long long* p) {
    unsigned long long v;
    asm volatile("ld.relaxed.gpu.global.b64 %0, [%1];" : "=l"(v) : "l"(p) : "memory");
    return v;
}
__device__ __forceinline__ void ld_pkt2(const unsigned long long* p, unsigned long long& a, unsigned long long& b) {
    asm volatile("ld.relaxed.gpu.global.v2.b64 {%0, %1}, [%2];" : "=l"(a), "=l"(b) : "l"(p) : "memory");
}
__device__ __forceinline__ float pkt_val(unsigned long long v) { return __uint_as_float((unsigned)v); }
__device__ __forceinline__ unsigned pkt_tag(unsigned long long v) { return (unsigned)(v >> 32); }

__device__ __forceinline__ float bf16r(float v) { return __bfloat162float(__float2bfloat16_rn(v)); }
__device__ __forceinline__ float bf_lo(uint32_t v) { return __uint_as_float(v << 16); }
__device__ __forceinline__ float bf_hi(uint32_t v) { return __uint_as_float(v & 0xffff0000u); }
__device__ __forceinline__ uint32_t pack_bf16(float lo, float hi) {
    uint32_t r;
    asm("cvt.rn.bf16x2.f32 %0, %1, %2;" : "=r"(r) : "f"(hi), "f"(lo));
    return r;
}
__device__ __forceinline__ float ex2(float x) {
    float r;
    asm("ex2.approx.ftz.f32 %0, %1;" : "=f"(r) : "f"(x));
    return r;
}
__device__ __forceinline__ void ldsm4(uint32_t addr, uint32_t (&r)[4]) {
    asm volatile("ldmatrix.sync.aligned.m8n8.x4.shared.b16 {%0,%1,%2,%3}, [%4];"
                 : "=r"(r[0]), "=r"(r[1]), "=r"(r[2]), "=r"(r[3]) : "r"(addr) : "memory");
}
__device__ __forceinline__ void ldsm4t(uint32_t addr, uint32_t (&r)[4]) {
    asm volatile("ldmatrix.sync.aligned.m8n8.x4.trans.shared.b16 {%0,%1,%2,%3}, [%4];"
                 : "=r"(r[0]), "=r"(r[1]), "=r"(r[2]), "=r"(r[3]) : "r"(addr) : "memory");
}
__device__ __forceinline__ void mma16816(float (&c)[4], const uint32_t (&a)[4], uint32_t b0, uint32_t b1) {
    asm volatile(
        "mma.sync.aligned.m16n8k16.row.col.f32.bf16.bf16.f32 {%0,%1,%2,%3}, {%4,%5,%6,%7}, {%8,%9}, {%0,%1,%2,%3};"
        : "+f"(c[0]), "+f"(c[1]), "+f"(c[2]), "+f"(c[3])
        : "r"(a[0]), "r"(a[1]), "r"(a[2]), "r"(a[3]), "r"(b0), "r"(b1));
}
__device__ __forceinline__ uint32_t movmat(uint32_t a) {
    uint32_t d;
    asm volatile("movmatrix.sync.aligned.m8n8.trans.b16 %0, %1;" : "=r"(d) : "r"(a));
    return d;
}
__device__ __forceinline__ void named_bar(int id, int n) {
    asm volatile("bar.sync %0, %1;" ::"r"(id), "r"(n) : "memory");
}

__device__ __forceinline__ void fma8(float (&acc)[8], const uint4& w, float xv) {
    acc[0] = fmaf(bf_lo(w.x), xv, acc[0]);
    acc[1] = fmaf(bf_hi(w.x), xv, acc[1]);
    acc[2] = fmaf(bf_lo(w.y), xv, acc[2]);
    acc[3] = fmaf(bf_hi(w.y), xv, acc[3]);
    acc[4] = fmaf(bf_lo(w.z), xv, acc[4]);
    acc[5] = fmaf(bf_hi(w.z), xv, acc[5]);
    acc[6] = fmaf(bf_lo(w.w), xv, acc[6]);
    acc[7] = fmaf(bf_hi(w.w), xv, acc[7]);
}
__device__ __forceinline__ float reduce8(float (&a)[8], int lane) {
    const bool h4 = lane & 16, h3 = lane & 8, h2 = lane & 4;
    float b[4], c[2];
#pragma unroll
    for (int j = 0; j < 4; j++) {
        float keep = h4 ? a[j + 4] : a[j], send = h4 ? a[j] : a[j + 4];
        b[j] = keep + __shfl_xor_sync(0xffffffffu, send, 16);
    }
#pragma unroll
    for (int j = 0; j < 2; j++) {
        float keep = h3 ? b[j + 2] : b[j], send = h3 ? b[j] : b[j + 2];
        c[j] = keep + __shfl_xor_sync(0xffffffffu, send, 8);
    }
    float keep = h2 ? c[1] : c[0], send = h2 ? c[0] : c[1];
    return keep + __shfl_xor_sync(0xffffffffu, send, 4);
}
__device__ __forceinline__ int reduce8_col(int lane) {
    return (lane & 3) * 8 + ((lane >> 4) & 1) * 4 + ((lane >> 3) & 1) * 2 + ((lane >> 2) & 1);
}

__device__ __forceinline__ void matvec_rows(int nr, const uint32_t* w32, const float* v, float& r0, float& r1) {
    uint32_t w[12];
#pragma unroll
    for (int j = 0; j < 12; j++)
        if (j < nr) w[j] = w32[j * 288];
#pragma unroll
    for (int j = 0; j < 12; j += 4)
        if (j < nr) {
            const float4 hv = *reinterpret_cast<const float4*>(v + j);
            r0 = fmaf(bf_lo(w[j]), hv.x, r0);
            r1 = fmaf(bf_hi(w[j]), hv.x, r1);
            r0 = fmaf(bf_lo(w[j + 1]), hv.y, r0);
            r1 = fmaf(bf_hi(w[j + 1]), hv.y, r1);
            r0 = fmaf(bf_lo(w[j + 2]), hv.z, r0);
            r1 = fmaf(bf_hi(w[j + 2]), hv.z, r1);
            r0 = fmaf(bf_lo(w[j + 3]), hv.w, r0);
            r1 = fmaf(bf_hi(w[j + 3]), hv.w, r1);
        }
}

struct Maps {
    CUtensorMap k, v, wq, wg, wu;
};

__global__ void __launch_bounds__(NTHREADS, 1)
fused_decode_kernel(const __grid_constant__ Maps maps, const __nv_bfloat16* __restrict__ x,
                    const __nv_bfloat16* __restrict__ wo, const __nv_bfloat16* __restrict__ wd,
                    __nv_bfloat16* __restrict__ out) {
    extern __shared__ unsigned char smem_raw[];
    unsigned char* smem = smem_raw + ((1024u - (smem_u32(smem_raw) & 1023u)) & 1023u);
    const int tid = threadIdx.x, lane = tid & 31;
    const int warp = __shfl_sync(0xffffffffu, tid >> 5, 0);
    const int cta = blockIdx.x;
    const bool att = cta < ATT_CTAS;
    const uint32_t sbase = smem_u32(smem);
    const uint32_t full0 = sbase + OFF_BAR, empty0 = full0 + 8 * NSLOT;
    float* red_s = reinterpret_cast<float*>(smem + OFF_RED);
    float* xn_s = reinterpret_cast<float*>(smem + OFF_XN);
    float* h_s = reinterpret_cast<float*>(smem + OFF_H);
    float* o_s = reinterpret_cast<float*>(smem + OFF_O);
    volatile int* pace_s = reinterpret_cast<volatile int*>(smem + OFF_PACE);
    TR(0);

    const int ring = att ? NSLOT : 9;
    auto wait_item = [&](int i, int sleep_ns) {
        for (int it = 0; pace_s[0] <= i && it < SPIN_LIMIT; it++) __nanosleep(sleep_ns);
        const int q = att ? i / NSLOT : i / 9, sl = i - q * ring;
        mbar_wait(full0 + 8 * sl, q & 1);
        return sl;
    };

    unsigned tag;
    if (warp == 9) {
        if (lane == 0) {
            for (int i = 0; i < NBAR; i++) mbar_init(full0 + 8 * i, i < NSLOT ? 1 : 4);
            pace_s[0] = 0;
            pace_s[1] = DEPTH;
            asm volatile("fence.mbarrier_init.release.cluster;" ::: "memory");
        }
        __syncwarp();
        asm volatile("bar.arrive 6, 320;" ::: "memory");
        tag = 0;
        if (lane == 0) {
            uint64_t pol;
            asm volatile("createpolicy.fractional.L2::evict_first.b64 %0, 1.0;" : "=l"(pol));
            uint64_t polw;
            asm volatile("createpolicy.fractional.L2::evict_normal.b64 %0, 1.0;" : "=l"(polw));
            const int nitems = att ? IT_END : 36;
            int slot = 0, ph = 0, lslot = 0, lph = 0, landed = 0, depth = DEPTH;
            int unit = att ? cta : ATT_CTAS + (cta - ATT_CTAS) * 4;
            int n = att ? 0 : NT, half = 0, j = 0;
#pragma unroll 1
            for (int i = 0; i < nitems; i++) {
                if (!att && j == 9) { j = 0; unit++; }
                if (i >= ring) mbar_wait(empty0 + 8 * slot, ph ^ 1);
                while (landed <= i - depth) {
                    mbar_wait(full0 + 8 * lslot, lph);
                    landed++;
                    if (++lslot == ring) { lslot = 0; lph ^= 1; }
                }
                const uint32_t bar = full0 + 8 * slot, dst = sbase + slot * SLOT;
                uint32_t bytes;
                const bool isq = att && i < IT_KV;
                if (!isq && n < NT && (half || j >= GU_MID || n != GU_AT + j * GU_EVERY)) {
                    const CUtensorMap* m = half ? &maps.v : &maps.k;
                    const int row = cta * 2048 + n * TP;
                    bytes = SLOT;
                    mbar_expect_tx(bar, SLOT);
                    tma2d(dst, m, 0, row, bar, pol);
                    tma2d(dst + SLOT / 2, m, 64, row, bar, pol);
                    n += half;
                    half ^= 1;
                } else if (j < 6) {
                    const CUtensorMap* m = isq ? &maps.wq : (j & 1) ? &maps.wu : &maps.wg;
                    bytes = 12288;
                    mbar_expect_tx(bar, 12288);
                    tma2d(dst, m, unit * 32, (isq ? i : j >> 1) * 192, bar, polw);
                    j += !isq;
                } else {
                    const int pc = j < 9 ? j - 6 : j - 9;
                    bytes = pc < 2 ? 12 * 1152 : 8 * 1152;
                    mbar_expect_tx(bar, bytes);
                    bulk_g2s(dst, reinterpret_cast<const char*>(j < 9 ? wd : wo) + (size_t)unit * WSL + pc * (12 * 1152), bytes,
                             bar, pol);
                    j++;
                }
                pace_s[0] = i + 1;
                if (PACE && att) depth = pace_s[1];
                if (TDEPTH && att && n == NT) depth = TDEPTH;
                if (++slot == ring) { slot = 0; ph ^= 1; }
            }
        }
        __syncwarp();
    } else if (warp == 10) {
        asm volatile("ld.relaxed.gpu.global.u32 %0, [%1];" : "=r"(tag) : "l"(&g_epoch) : "memory");
    } else {
        uint32_t xs[9];
#pragma unroll
        for (int i = 0; i < 9; i++) xs[i] = __ldg(reinterpret_cast<const uint32_t*>(x) + lane + 32 * i);
        asm volatile("ld.relaxed.gpu.global.u32 %0, [%1];" : "=r"(tag) : "l"(&g_epoch) : "memory");
        float s = 0.f;
#pragma unroll
        for (int i = 0; i < 9; i++) s += bf_lo(xs[i]) + bf_hi(xs[i]);
#pragma unroll
        for (int o = 16; o; o >>= 1) s += __shfl_xor_sync(0xffffffffu, s, o);
        const float mean = s * (1.f / D_MODEL);
        float vs = 0.f;
#pragma unroll
        for (int i = 0; i < 9; i++) {
            float a = bf_lo(xs[i]) - mean, b = bf_hi(xs[i]) - mean;
            vs += a * a + b * b;
        }
#pragma unroll
        for (int o = 16; o; o >>= 1) vs += __shfl_xor_sync(0xffffffffu, vs, o);
        const float mb = bf16r(mean);
        const float den = bf16r(sqrtf(bf16r(bf16r(vs * (1.f / D_MODEL)) + 1e-5f)));
        uint32_t mine = xs[0];
#pragma unroll
        for (int i = 1; i < 9; i++) mine = (warp == i) ? xs[i] : mine;
        *reinterpret_cast<float2*>(xn_s + 2 * tid) =
            make_float2(bf16r(bf16r(bf_lo(mine) - mb) / den), bf16r(bf16r(bf_hi(mine) - mb) / den));
        TR(15);
        named_bar(6, 320);
    }
    tag += 1;

    if (att && warp < 8) {
        float acc[8] = {0.f, 0.f, 0.f, 0.f, 0.f, 0.f, 0.f, 0.f};
#pragma unroll
        for (int i = 0; i < 9; i++) {
            if (i % 3 == 0) mbar_wait(full0 + 8 * (i / 3), 0);
            fma8(acc, lds128(sbase + (i / 3) * SLOT + (i % 3) * 4096 + tid * 16), xn_s[(tid >> 2) + 64 * i]);
        }
        red_s[warp * 32 + reduce8_col(lane)] = reduce8(acc, lane);
        named_bar(1, 256);
        if (warp == 0) {
            float s = 0.f;
#pragma unroll
            for (int w = 0; w < 8; w++) s += red_s[w * 32 + lane];
            st_pkt(&g_q[cta * 32 + lane], pack_pkt(bf16r(s), tag));
        } else if (warp == 1 && lane < 3) {
            mbar_arrive4(empty0 + 8 * lane);
        }
        TR(1);
    } else if (att && warp == 10) {
        const unsigned long long* src = &g_q[(cta >> 3) * 256 + lane * 2];
        unsigned pend = 0xf;
        for (int it = 0; pend && it < SPIN_LIMIT; it++) {
            unsigned long long a[4], b[4];
#pragma unroll
            for (int u = 0; u < 4; u++)
                if (pend >> u & 1) ld_pkt2(src + u * 64, a[u], b[u]);
#pragma unroll
            for (int u = 0; u < 4; u++)
                if ((pend >> u & 1) && pkt_tag(a[u]) == tag && pkt_tag(b[u]) == tag) {
                    pend &= ~(1u << u);
                    reinterpret_cast<uint32_t*>(smem + OFF_Q)[u * 32 + lane] = ((unsigned)a[u] >> 16) | ((unsigned)b[u] & 0xffff0000u);
                }
        }
        __syncwarp();
        asm volatile("bar.arrive 4, %0;" ::"n"(32 * AW + 32) : "memory");
        if (PACE && lane == 0) {
            for (int k = 0; k < PACE_N; k++) {
                for (int it = 0; pace_s[0] < PACE_I0 + PACE_STEP * k && it < SPIN_LIMIT; it++) __nanosleep(100);
                unsigned prog;
                asm volatile("atom.relaxed.gpu.global.add.u32 %0, [%1], 1;" : "=r"(prog) : "l"(&g_prog[0]) : "memory");
                const int lead = k * ATT_CTAS + ATT_CTAS / 2 - (int)prog;
                pace_s[1] = lead > PACE_TH ? DMIN : lead < -2 * PACE_TH ? DMAX : lead < -PACE_TH ? DEPTH + 1 : DEPTH;
            }
        }
        __syncwarp();
    }

    float r0 = 0.f, r1 = 0.f;
    const int nunits = att ? 1 : 4;
#pragma unroll 1
    for (int u = 0; u < nunits; u++) {
        if (warp >= 4 && warp < 8) {
            const int ft = tid - 128;
            float ag[8] = {0.f, 0.f, 0.f, 0.f, 0.f, 0.f, 0.f, 0.f};
            float au[8] = {0.f, 0.f, 0.f, 0.f, 0.f, 0.f, 0.f, 0.f};
#pragma unroll 1
            for (int pc = 0; pc < 3; pc++) {
                float xv[6];
#pragma unroll
                for (int i = 0; i < 6; i++) xv[i] = xn_s[pc * 192 + (ft >> 2) + 32 * i];
                const int sg = wait_item(att ? item_of_w(2 * pc) : 9 * u + 2 * pc, 200);
#pragma unroll
                for (int i = 0; i < 6; i++) fma8(ag, lds128(sbase + sg * SLOT + ft * 16 + i * 2048), xv[i]);
                __syncwarp();
                if (lane == 0) mbar_arrive(empty0 + 8 * sg);
                const int su = wait_item(att ? item_of_w(2 * pc + 1) : 9 * u + 2 * pc + 1, 200);
#pragma unroll
                for (int i = 0; i < 6; i++) fma8(au, lds128(sbase + su * SLOT + ft * 16 + i * 2048), xv[i]);
                __syncwarp();
                if (lane == 0) mbar_arrive(empty0 + 8 * su);
            }
            const int col = reduce8_col(lane);
            red_s[256 + (warp - 4) * 32 + col] = reduce8(ag, lane);
            red_s[512 + (warp - 4) * 32 + col] = reduce8(au, lane);
            named_bar(3, 128);
            if (warp == 4) {
                float g = 0.f, up = 0.f;
#pragma unroll
                for (int w = 0; w < 4; w++) {
                    g += red_s[256 + w * 32 + lane];
                    up += red_s[512 + w * 32 + lane];
                }
                g = bf16r(g);
                up = bf16r(up);
                const float sg = bf16r(g / (1.f + __expf(-g)));
                h_s[lane] = bf16r(sg * up);
                TRW(2);
            }
        } else if (att && warp < AW) {
            named_bar(4, 32 * AW + 32);
            TR(3);
            const int g = lane >> 2, t = lane & 3;
            uint32_t qf[8][2];
            {
                const uint32_t* q32 = reinterpret_cast<const uint32_t*>(smem + OFF_Q) + (g & 1) * 64 + t;
#pragma unroll
                for (int ks = 0; ks < 8; ks++) {
                    qf[ks][0] = q32[ks * 8];
                    qf[ks][1] = q32[ks * 8 + 4];
                }
            }
            const int lr = lane & 7, mi = lane >> 3;
            const uint32_t koff = sbase + ((mi & 1) * 8 + lr) * 128 + (((mi >> 1) ^ lr) << 4);
            const uint32_t voff = sbase + ((mi >> 1) * 8 + lr) * 128 + (((mi & 1) ^ lr) << 4);
            float o[8][4];
#pragma unroll
            for (int i = 0; i < 8; i++) o[i][0] = o[i][1] = o[i][2] = o[i][3] = 0.f;
            float m0 = -INFINITY, m1 = -INFINITY, l0 = 0.f, l1 = 0.f;
            constexpr float SCALE = 0.08838834764831845f;
#pragma unroll 1
            for (int n = warp; n < NT; n += AW) {
                const int ik = item_of_tile(n);
                const int ks_ = wait_item(ik, 50);
                const uint32_t kaddr = koff + ks_ * SLOT;
                float sc[4][4];
#pragma unroll
                for (int i = 0; i < 4; i++) sc[i][0] = sc[i][1] = sc[i][2] = sc[i][3] = 0.f;
#pragma unroll
                for (int ks = 0; ks < 8; ks++) {
#pragma unroll
                    for (int i = 0; i < 4; i++) {
                        uint32_t a[4];
                        ldsm4((kaddr ^ ((ks & 3) << 5)) + (ks >> 2) * (SLOT / 2) + i * 2048, a);
                        mma16816(sc[i], a, qf[ks][0], qf[ks][1]);
                    }
                }
                if (lane == 0) mbar_arrive4(empty0 + 8 * ks_);
                float v[4];
#pragma unroll
                for (int j = 0; j < 4; j++) {
                    float a = (t & 1) ? sc[1][j] : sc[0][j];
                    float b = (t & 1) ? sc[3][j] : sc[2][j];
                    v[j] = bf16r(bf16r((t & 2) ? b : a) * SCALE);
                }
                float x0 = fmaxf(v[0], v[2]), x1 = fmaxf(v[1], v[3]);
#pragma unroll
                for (int off = 4; off <= 16; off <<= 1) {
                    x0 = fmaxf(x0, __shfl_xor_sync(0xffffffffu, x0, off));
                    x1 = fmaxf(x1, __shfl_xor_sync(0xffffffffu, x1, off));
                }
                const float n0 = fmaxf(m0, x0), n1 = fmaxf(m1, x1);
                const float a0 = ex2((m0 - n0) * LOG2E), a1 = ex2((m1 - n1) * LOG2E);
                m0 = n0;
                m1 = n1;
                const float p0 = ex2((v[0] - n0) * LOG2E), p1 = ex2((v[1] - n1) * LOG2E);
                const float p2 = ex2((v[2] - n0) * LOG2E), p3 = ex2((v[3] - n1) * LOG2E);
                l0 = fmaf(l0, a0, p0 + p2);
                l1 = fmaf(l1, a1, p1 + p3);
                const uint32_t blo = movmat(pack_bf16(p0, p1));
                const uint32_t bhi = movmat(pack_bf16(p2, p3));
#pragma unroll
                for (int i = 0; i < 8; i++) {
                    o[i][0] *= a0;
                    o[i][1] *= a1;
                    o[i][2] *= a0;
                    o[i][3] *= a1;
                }
                const int vs_ = wait_item(ik + 1, 50);
                const uint32_t vaddr = voff + vs_ * SLOT;
#pragma unroll
                for (int i = 0; i < 4; i++) {
                    const uint32_t b0 = ((g >> 1) == i) ? blo : 0u, b1 = ((g >> 1) == i) ? bhi : 0u;
#pragma unroll
                    for (int md = 0; md < 8; md++) {
                        uint32_t a[4];
                        ldsm4t((vaddr ^ ((md & 3) << 5)) + (md >> 2) * (SLOT / 2) + i * 2048, a);
                        mma16816(o[md], a, b0, b1);
                    }
                }
                if (lane == 0) mbar_arrive4(empty0 + 8 * vs_);
            }
            TR(4);
            float w0 = m0, w1 = m1;
#pragma unroll
            for (int off = 1; off <= 2; off <<= 1) {
                w0 = fmaxf(w0, __shfl_xor_sync(0xffffffffu, w0, off));
                w1 = fmaxf(w1, __shfl_xor_sync(0xffffffffu, w1, off));
            }
            const float s0 = ex2((m0 - w0) * LOG2E), s1 = ex2((m1 - w1) * LOG2E);
            l0 *= s0;
            l1 *= s1;
#pragma unroll
            for (int off = 1; off <= 16; off <<= 1) {
                l0 += __shfl_xor_sync(0xffffffffu, l0, off);
                l1 += __shfl_xor_sync(0xffffffffu, l1, off);
            }
            float* mo = reinterpret_cast<float*>(smem + OFF_MO);
            float* ml = reinterpret_cast<float*>(smem + OFF_ML);
#pragma unroll
            for (int md = 0; md < 8; md++) {
                float a = o[md][0] * s0, b = o[md][1] * s1, c = o[md][2] * s0, d = o[md][3] * s1;
                const bool u1 = t & 1, u2 = t & 2;
                float k0 = u2 ? c : a, k1 = u2 ? d : b, e0 = u2 ? a : c, e1 = u2 ? b : d;
                k0 += __shfl_xor_sync(0xffffffffu, e0, 2);
                k1 += __shfl_xor_sync(0xffffffffu, e1, 2);
                float k = u1 ? k1 : k0, e = u1 ? k0 : k1;
                k += __shfl_xor_sync(0xffffffffu, e, 1);
                mo[warp * 256 + (t & 1) * 128 + md * 16 + g + (t >> 1) * 8] = k;
            }
            if (lane == 0) {
                ml[warp * 4 + 0] = w0; ml[warp * 4 + 1] = l0; ml[warp * 4 + 2] = w1; ml[warp * 4 + 3] = l1;
            }
            named_bar(7, 32 * AW);
#pragma unroll 1
            for (int sl = warp; sl < 8; sl += AW) {
                const int hsel = sl >> 2;
                float M = -INFINITY;
#pragma unroll
                for (int w = 0; w < AW; w++) M = fmaxf(M, ml[w * 4 + hsel * 2]);
                float acc = 0.f, L = 0.f;
#pragma unroll
                for (int w = 0; w < AW; w++) {
                    const float sc = ex2((ml[w * 4 + hsel * 2] - M) * LOG2E);
                    acc = fmaf(mo[w * 256 + sl * 32 + lane], sc, acc);
                    L = fmaf(ml[w * 4 + hsel * 2 + 1], sc, L);
                }
                if (sl != (cta & 7)) {
                    st_pkt(&g_po[cta][sl][lane], pack_pkt(acc, tag));
                    if (lane < 8) st_pkt2(&g_po[cta][sl][32 + 2 * lane], pack_pkt(M, tag), pack_pkt(L, tag));
                } else {
                    float* own = reinterpret_cast<float*>(smem + OFF_OWN);
                    own[lane] = acc;
                    if (lane == 0) { own[32] = M; own[33] = L; }
                    asm volatile("bar.arrive 5, 64;" ::: "memory");
                }
            }
            TR(5);
        }
        if (warp < 9) {
            named_bar(2, 288);
#pragma unroll
            for (int pc = 0; pc < 3; pc++) {
                const int sl = wait_item(att ? item_of_w(6 + pc) : 9 * u + 6 + pc, 50);
                const uint32_t* w32 = reinterpret_cast<const uint32_t*>(smem + sl * SLOT) + tid;
                matvec_rows(pc < 2 ? 12 : 8, w32, h_s + pc * 12, r0, r1);
            }
            if (!att) {
                named_bar(2, 288);
                if (tid < 3) mbar_arrive4(empty0 + 8 * (6 + tid));
            }
        }
    }
    TR(6);
    if (att) {
        if (warp == 10) {
            const int hb = cta & ~7, s = cta & 7;
            unsigned long long a[8], b[8];
            unsigned pend = lane <= 16 ? (0xffu & ~(1u << s)) : 0u;
#pragma unroll
            for (int j = 0; j < 8; j++) a[j] = b[j] = 0ull;
            named_bar(5, 64);
            for (int it = 0; pend && it < SPIN_LIMIT; it++) {
                if (POLL_NS && it) __nanosleep(POLL_NS);
#pragma unroll
                for (int j = 0; j < 8; j++)
                    if (pend >> j & 1) ld_pkt2(&g_po[hb + j][s][lane * 2], a[j], b[j]);
#pragma unroll
                for (int j = 0; j < 8; j++)
                    if (pkt_tag(a[j]) == tag && pkt_tag(b[j]) == tag) pend &= ~(1u << j);
            }
            __syncwarp();
            {
                const float2 own = *reinterpret_cast<const float2*>(smem + OFF_OWN + (lane <= 16 ? lane : 0) * 8);
#pragma unroll
                for (int j = 0; j < 8; j++)
                    if (j == s) {
                        a[j] = __float_as_uint(own.x);
                        b[j] = __float_as_uint(own.y);
                    }
            }
            float M = -INFINITY;
#pragma unroll
            for (int j = 0; j < 8; j++) M = fmaxf(M, pkt_val(a[j]));
            float L = 0.f, sc[8];
#pragma unroll
            for (int j = 0; j < 8; j++) {
                sc[j] = ex2((pkt_val(a[j]) - M) * LOG2E);
                L = fmaf(pkt_val(b[j]), sc[j], L);
            }
            L = __shfl_sync(0xffffffffu, L, 16);
            float acc0 = 0.f, acc1 = 0.f;
#pragma unroll
            for (int j = 0; j < 8; j++) {
                const float w = __shfl_sync(0xffffffffu, sc[j], 16);
                acc0 = fmaf(pkt_val(a[j]), w, acc0);
                acc1 = fmaf(pkt_val(b[j]), w, acc1);
            }
            if (lane < 16) *reinterpret_cast<float2*>(o_s + lane * 2) = make_float2(bf16r(acc0 / L), bf16r(acc1 / L));
            TRW(11);
            __syncwarp();
            asm volatile("bar.arrive 0, 320;" ::: "memory");
        } else if (warp < 9) {
            named_bar(0, 320);
#pragma unroll
            for (int pc = 0; pc < 3; pc++) {
                const int sl = wait_item(item_of_w(9 + pc), 50);
                const uint32_t* w32 = reinterpret_cast<const uint32_t*>(smem + sl * SLOT) + tid;
                if (pc == 2) TR(12);
                matvec_rows(pc < 2 ? 12 : 8, w32, o_s + pc * 12, r0, r1);
            }
        }
    }
    if (warp < 9)
        asm volatile("red.relaxed.gpu.global.add.v4.f32 [%0], {%1, %2, %3, %4};"
                     ::"l"(&g_acc[cta % NCOPY][tid]), "f"(r0), "f"(r1), "f"(1.0f), "f"(0.0f) : "memory");
    TR(8);

    if (!att && tid < 72 * NCOPY) {
        const int slot = (cta - ATT_CTAS) * 72 + tid / NCOPY, copy = tid % NCOPY;
        float4* src = &g_acc[copy][slot];
        const uint32_t xv = __ldg(reinterpret_cast<const uint32_t*>(x) + slot);
        unsigned long long a, b;
        for (int it = 0; it < SPIN_LIMIT; it++) {
            ld_pkt2(reinterpret_cast<const unsigned long long*>(src), a, b);
            const float cnt = pkt_val(b);
            if (cnt == (float)(NCTA / NCOPY)) break;
            if (cnt < (float)(NCTA / NCOPY / 2)) __nanosleep(200);
        }
        __syncwarp();
        float s0 = pkt_val(a), s1 = __uint_as_float(pkt_tag(a));
#pragma unroll
        for (int off = 1; off < NCOPY; off <<= 1) {
            s0 += __shfl_xor_sync(0xffffffffu, s0, off);
            s1 += __shfl_xor_sync(0xffffffffu, s1, off);
        }
        if (copy == 0) reinterpret_cast<uint32_t*>(out)[slot] = pack_bf16(bf_lo(xv) + s0, bf_hi(xv) + s1);
        *src = make_float4(0.f, 0.f, 0.f, 0.f);
        if (cta == ATT_CTAS && tid == 0) { g_epoch = tag; g_prog[0] = 0; }
    }
    TR(9);
}

typedef CUresult (*EncodeFn)(CUtensorMap*, CUtensorMapDataType, cuuint32_t, void*, const cuuint64_t*, const cuuint64_t*,
                             const cuuint32_t*, const cuuint32_t*, CUtensorMapInterleave, CUtensorMapSwizzle,
                             CUtensorMapL2promotion, CUtensorMapFloatOOBfill);

void make_map(EncodeFn enc, CUtensorMap* m, void* base, uint64_t cols, uint64_t rows, uint32_t bc, uint32_t br,
              CUtensorMapSwizzle sw, CUtensorMapL2promotion promo) {
    cuuint64_t gd[2] = {cols, rows};
    cuuint64_t gs[1] = {cols * 2};
    cuuint32_t bx[2] = {bc, br};
    cuuint32_t es[2] = {1, 1};
    enc(m, CU_TENSOR_MAP_DATA_TYPE_BFLOAT16, 2, base, gd, gs, bx, es, CU_TENSOR_MAP_INTERLEAVE_NONE, sw, promo,
        CU_TENSOR_MAP_FLOAT_OOB_FILL_NONE);
}

}

#define W_PROMO CU_TENSOR_MAP_L2_PROMOTION_L2_256B
#define KV_PROMO CU_TENSOR_MAP_L2_PROMOTION_L2_256B

extern "C" void kernel_launch(void* const* d_in, const int* in_sizes, int n_in, void* d_out, int out_size) {
    (void)in_sizes; (void)n_in; (void)out_size;
    static EncodeFn enc = nullptr;
    if (!enc) {
        void* fn = nullptr;
        cudaDriverEntryPointQueryResult qr;
        cudaGetDriverEntryPoint("cuTensorMapEncodeTiled", &fn, cudaEnableDefault, &qr);
        enc = (EncodeFn)fn;
        cudaFuncSetAttribute(fused_decode_kernel, cudaFuncAttributeMaxDynamicSharedMemorySize, SMEM_BYTES);
    }
    Maps maps;
    make_map(enc, &maps.k, d_in[1], 128, 16 * 16384, 64, TP, CU_TENSOR_MAP_SWIZZLE_128B, KV_PROMO);
    make_map(enc, &maps.v, d_in[2], 128, 16 * 16384, 64, TP, CU_TENSOR_MAP_SWIZZLE_128B, KV_PROMO);
    make_map(enc, &maps.wq, d_in[3], NQ, D_MODEL, 32, 192, CU_TENSOR_MAP_SWIZZLE_NONE, W_PROMO);
    make_map(enc, &maps.wg, d_in[6], FF, D_MODEL, 32, 192, CU_TENSOR_MAP_SWIZZLE_NONE, W_PROMO);
    make_map(enc, &maps.wu, d_in[7], FF, D_MODEL, 32, 192, CU_TENSOR_MAP_SWIZZLE_NONE, W_PROMO);
    fused_decode_kernel<<<NCTA, NTHREADS, SMEM_BYTES>>>(maps, (const __nv_bfloat16*)d_in[0], (const __nv_bfloat16*)d_in[4],
                                                        (const __nv_bfloat16*)d_in[8], (__nv_bfloat16*)d_out);
}
```

```cpp
#include <cuda_runtime.h>
#include <cuda.h>
#include <cuda_bf16.h>
#include <stdint.h>

namespace {

constexpr int D_MODEL = 576;
constexpr int NQ = 4096;
constexpr int FF = 4608;

constexpr int NCTA = 132;
constexpr int ATT_CTAS = 128;
constexpr int NTHREADS = 352;

constexpr int AW = 4;
constexpr int TP = 64;
constexpr int NT = 2048 / TP;
constexpr int SLOT = TP * 256;
constexpr int NSLOT = 13;
constexpr int CPB = 192 * 64;
constexpr int RPB = 8 * 1152;

#define DEPTH 6
#define TDEPTH 5
#define BW_EFF 0.9394
#define T_OFF 500
#define XSLOW 10
#define POLL_AT 5
#define QPOLL_AT 6
#define FIN_X 110
#define DRY 1
constexpr int KG = 4;

constexpr int IT_KV = 3, IT_W = IT_KV + 2 * NT, IT_END = IT_W + 14, XRING = 10;
static_assert(NT % KG == 0 && POLL_AT >= 1, "");
__device__ constexpr int item_of_tile(int n) { return IT_KV + 2 * (n - n % KG) + n % KG; }
__device__ constexpr int item_of_w(int j) { return IT_W + j; }

constexpr int OFF_RED = NSLOT * SLOT;
constexpr int OFF_XN = OFF_RED + 3 * 4 * 32 * 4;
constexpr int OFF_Q = OFF_XN + D_MODEL * 2;
constexpr int OFF_H = OFF_Q + 512;
constexpr int OFF_O = OFF_H + 64;
constexpr int OFF_OWN = OFF_O + 64;
constexpr int OFF_MO = OFF_OWN + 144;
constexpr int OFF_ML = OFF_MO + AW * 256 * 4;
constexpr int OFF_BAR = OFF_ML + AW * 16;
constexpr int OFF_PACE = OFF_BAR + 2 * NSLOT * 8;
constexpr int SMEM_BYTES = OFF_PACE + 16 + 1024;
static_assert(SMEM_BYTES <= 232448, "smem");

constexpr int NCOPY = 4;
constexpr int SPIN_LIMIT = 1 << 17;
constexpr int WAIT_LIMIT = 1 << 17;
constexpr float LOG2E = 1.4426950408889634f;

__device__ unsigned g_epoch;
__device__ __align__(128) unsigned long long g_q[NQ];
__device__ __align__(128) unsigned long long g_po[ATT_CTAS][8][48];
__device__ __align__(128) float4 g_acc[NCOPY][288];
#define TR(i)
#define TRW(i)

__device__ __forceinline__ uint32_t smem_u32(const void* p) { return (uint32_t)__cvta_generic_to_shared(p); }
__device__ __forceinline__ void mbar_init(uint32_t bar, uint32_t cnt) {
    asm volatile("mbarrier.init.shared::cta.b64 [%0], %1;" ::"r"(bar), "r"(cnt) : "memory");
}
__device__ __forceinline__ void mbar_expect_tx(uint32_t bar, uint32_t bytes) {
    asm volatile("mbarrier.arrive.expect_tx.shared::cta.b64 _, [%0], %1;" ::"r"(bar), "r"(bytes) : "memory");
}
__device__ __forceinline__ void mbar_arrive(uint32_t bar) {
    asm volatile("mbarrier.arrive.shared::cta.b64 _, [%0];" ::"r"(bar) : "memory");
}
__device__ __forceinline__ void mbar_arrive4(uint32_t bar) {
    asm volatile("mbarrier.arrive.shared::cta.b64 _, [%0], 4;" ::"r"(bar) : "memory");
}
__device__ __forceinline__ void mbar_wait(uint32_t bar, uint32_t parity) {
    for (int it = 0; it < WAIT_LIMIT; it++) {
        uint32_t ok;
        asm volatile(
            "{\n.reg .pred p;\n"
            "mbarrier.try_wait.parity.shared::cta.b64 p, [%1], %2, %3;\n"
            "selp.u32 %0, 1, 0, p;\n}\n"
            : "=r"(ok) : "r"(bar), "r"(parity), "r"(1000) : "memory");
        if (ok) break;
    }
}
__device__ __forceinline__ void mbar_spin(uint32_t bar, uint32_t parity) {
    for (int it = 0; it < (1 << 22); it++) {
        uint32_t ok;
        asm volatile(
            "{\n.reg .pred p;\n"
            "mbarrier.test_wait.parity.shared::cta.b64 p, [%1], %2;\n"
            "selp.u32 %0, 1, 0, p;\n}\n"
            : "=r"(ok) : "r"(bar), "r"(parity) : "memory");
        if (ok) break;
    }
}
__device__ __forceinline__ unsigned long long gtime() {
    unsigned long long t;
    asm volatile("mov.u64 %0, %globaltimer;" : "=l"(t));
    return t;
}
__device__ __forceinline__ void tma2d(uint32_t dst, const CUtensorMap* map, int c0, int c1, uint32_t bar, uint64_t pol) {
    asm volatile(
        "cp.async.bulk.tensor.2d.shared::cluster.global.mbarrier::complete_tx::bytes.L2::cache_hint "
        "[%0], [%1, {%3, %4}], [%2], %5;"
        ::"r"(dst), "l"(map), "r"(bar), "r"(c0), "r"(c1), "l"(pol) : "memory");
}
__device__ __forceinline__ unsigned long long pack_pkt(float v, unsigned tag) {
    return (unsigned long long)__float_as_uint(v) | ((unsigned long long)tag << 32);
}
__device__ __forceinline__ void st_pkt(unsigned long long* p, unsigned long long v) {
    asm volatile("st.relaxed.gpu.global.b64 [%0], %1;" ::"l"(p), "l"(v) : "memory");
}
__device__ __forceinline__ void st_pkt2(unsigned long long* p, unsigned long long a, unsigned long long b) {
    asm volatile("st.relaxed.gpu.global.v2.b64 [%0], {%1, %2};" ::"l"(p), "l"(a), "l"(b) : "memory");
}
__device__ __forceinline__ void ld_pkt2(const unsigned long long* p, unsigned long long& a, unsigned long long& b) {
    asm volatile("ld.relaxed.gpu.global.v2.b64 {%0, %1}, [%2];" : "=l"(a), "=l"(b) : "l"(p) : "memory");
}
__device__ __forceinline__ float pkt_val(unsigned long long v) { return __uint_as_float((unsigned)v); }
__device__ __forceinline__ unsigned pkt_tag(unsigned long long v) { return (unsigned)(v >> 32); }

__device__ __forceinline__ float bf16r(float v) { return __bfloat162float(__float2bfloat16_rn(v)); }
__device__ __forceinline__ float bf_lo(uint32_t v) { return __uint_as_float(v << 16); }
__device__ __forceinline__ float bf_hi(uint32_t v) { return __uint_as_float(v & 0xffff0000u); }
__device__ __forceinline__ uint32_t pack_bf16(float lo, float hi) {
    uint32_t r;
    asm("cvt.rn.bf16x2.f32 %0, %1, %2;" : "=r"(r) : "f"(hi), "f"(lo));
    return r;
}
__device__ __forceinline__ float ex2(float x) {
    float r;
    asm("ex2.approx.ftz.f32 %0, %1;" : "=f"(r) : "f"(x));
    return r;
}
__device__ __forceinline__ void ldsm4(uint32_t addr, uint32_t (&r)[4]) {
    asm volatile("ldmatrix.sync.aligned.m8n8.x4.shared.b16 {%0,%1,%2,%3}, [%4];"
                 : "=r"(r[0]), "=r"(r[1]), "=r"(r[2]), "=r"(r[3]) : "r"(addr) : "memory");
}
__device__ __forceinline__ void ldsm4t(uint32_t addr, uint32_t (&r)[4]) {
    asm volatile("ldmatrix.sync.aligned.m8n8.x4.trans.shared.b16 {%0,%1,%2,%3}, [%4];"
                 : "=r"(r[0]), "=r"(r[1]), "=r"(r[2]), "=r"(r[3]) : "r"(addr) : "memory");
}
__device__ __forceinline__ void mma16816(float (&c)[4], const uint32_t (&a)[4], uint32_t b0, uint32_t b1) {
    asm volatile(
        "mma.sync.aligned.m16n8k16.row.col.f32.bf16.bf16.f32 {%0,%1,%2,%3}, {%4,%5,%6,%7}, {%8,%9}, {%0,%1,%2,%3};"
        : "+f"(c[0]), "+f"(c[1]), "+f"(c[2]), "+f"(c[3])
        : "r"(a[0]), "r"(a[1]), "r"(a[2]), "r"(a[3]), "r"(b0), "r"(b1));
}
__device__ __forceinline__ uint32_t movmat(uint32_t a) {
    uint32_t d;
    asm volatile("movmatrix.sync.aligned.m8n8.trans.b16 %0, %1;" : "=r"(d) : "r"(a));
    return d;
}
__device__ __forceinline__ void named_bar(int id, int n) {
    asm volatile("bar.sync %0, %1;" ::"r"(id), "r"(n) : "memory");
}
__device__ __forceinline__ void named_arrive(int id, int n) {
    asm volatile("bar.arrive %0, %1;" ::"r"(id), "r"(n) : "memory");
}

struct Maps {
    CUtensorMap k, v, wq, wg, wu, wd, wo;
};

__global__ void __launch_bounds__(NTHREADS, 1)
fused_decode_kernel(const __grid_constant__ Maps maps, const __nv_bfloat16* __restrict__ x,
                    __nv_bfloat16* __restrict__ out, const unsigned tau) {
    extern __shared__ unsigned char smem_raw[];
    const uint32_t sbase = (smem_u32(smem_raw) + 1023u) & ~1023u;
    const uint32_t full0 = sbase + OFF_BAR, empty0 = full0 + 8 * NSLOT;
    const int tid = threadIdx.x, cta = blockIdx.x;
    const bool att = cta < ATT_CTAS;
    unsigned char* smem = smem_raw + (sbase - smem_u32(smem_raw));
    volatile int* issued_s = reinterpret_cast<volatile int*>(smem + OFF_PACE);
    const int ring = att ? NSLOT : XRING;
    if (tid >= 288 && tid < 320) {
        if (tid != 288) asm volatile("exit;");
        const unsigned t0 = (unsigned)gtime();
        uint64_t pol, polw;
#pragma unroll
        for (int b = 0; b < 3; b++) mbar_init(full0 + 8 * b, 1);
        asm volatile("fence.mbarrier_init.release.cluster;" ::: "memory");
        asm volatile("createpolicy.fractional.L2::evict_normal.b64 %0, 1.0;" : "=l"(polw));
        int unit = att ? cta : ATT_CTAS + (cta - ATT_CTAS) * 4;
#pragma unroll
        for (int b = 0; b < 3; b++) {
            mbar_expect_tx(full0 + 8 * b, CPB);
            tma2d(sbase + b * SLOT, att ? &maps.wq : (b & 1) ? &maps.wu : &maps.wg, unit * 32, (att ? b : b >> 1) * 192,
                  full0 + 8 * b, polw);
        }
#pragma unroll 1
        for (int i = 3; i < 2 * NSLOT; i++) mbar_init(full0 + 8 * i, i < NSLOT ? 1 : 4);
        *issued_s = 3;
        asm volatile("fence.mbarrier_init.release.cluster;" ::: "memory");
        named_arrive(6, NTHREADS);
        asm volatile("createpolicy.fractional.L2::evict_first.b64 %0, 1.0;" : "=l"(pol));
        const int nitems = att ? IT_END : 4 * XRING;
        int slot = 3, ph = 0, lslot = 0, lph = 0, landed = 0, depth = DEPTH;
        unsigned due = T_OFF << 4;
        int n = att ? 0 : NT, half = 0, j = att ? 0 : 3;
#pragma unroll 1
        for (int i = 3; i < nitems; i++) {
            if (!att && j == XRING) { j = 0; unit++; }
            const uint32_t bar = full0 + 8 * slot, dst = sbase + slot * SLOT;
            if (i >= ring) mbar_wait(empty0 + 8 * slot, ph ^ 1);
            while (landed <= i - depth) {
                mbar_wait(full0 + 8 * lslot, lph);
                landed++;
                if (++lslot == ring) { lslot = 0; lph ^= 1; }
            }
            if (n < NT || !att)
                for (int it = 0; (int)((unsigned)gtime() - t0 - (due >> 4)) < 0 && it < (1 << 22); it++) {}
            uint32_t bytes;
            if (n < NT) {
                const CUtensorMap* m = half >= KG ? &maps.v : &maps.k;
                const int row = cta * 2048 + (n + (half >= KG ? half - KG : half)) * TP;
                bytes = SLOT;
                mbar_expect_tx(bar, SLOT);
                tma2d(dst, m, 0, row, bar, pol);
                tma2d(dst + SLOT / 2, m, 64, row, bar, pol);
                if (++half == 2 * KG) { half = 0; n += KG; }
            } else if (j < 6) {
                const CUtensorMap* m = (j & 1) ? &maps.wu : &maps.wg;
                bytes = CPB;
                mbar_expect_tx(bar, CPB);
                tma2d(dst, m, unit * 32, (j >> 1) * 192, bar, polw);
                j++;
            } else {
                bytes = RPB;
                mbar_expect_tx(bar, RPB);
                tma2d(dst, j < 10 ? &maps.wd : &maps.wo, 0, unit * 288 + ((j - 6) & 3) * 72, bar, pol);
                j++;
            }
            due += (bytes >> 10) * (att ? tau : tau * XSLOW / 4);
            *issued_s = i + 1;
            if (n == NT) depth = TDEPTH;
            if (++slot == ring) { slot = 0; ph ^= 1; }
        }
        asm volatile("exit;");
    }
    const int lane = tid & 31;
    const int warp = __shfl_sync(0xffffffffu, tid >> 5, 0);
    float* red_s = reinterpret_cast<float*>(smem + OFF_RED);
    uint32_t* xn32 = reinterpret_cast<uint32_t*>(smem + OFF_XN);
    const int g = lane >> 2, t = lane & 3;
    const int lr = lane & 7, mi = lane >> 3;
    TR(0);

    auto wait_item = [&](int i, int sleep_ns) {
        for (int it = 0; *issued_s <= i && it < SPIN_LIMIT; it++) __nanosleep(sleep_ns);
        const int q = att ? i / NSLOT : i / XRING, sl = i - q * ring;
        if (sleep_ns == 20) mbar_spin(full0 + 8 * sl, q & 1); else mbar_wait(full0 + 8 * sl, q & 1);
        return sl;
    };

    unsigned tag = 0;
    asm volatile("ld.relaxed.gpu.global.u32 %0, [%1];" : "=r"(tag) : "l"(&g_epoch) : "memory");
    if (warp < 9) {
        uint32_t xs[9];
#pragma unroll
        for (int i = 0; i < 9; i++) xs[i] = __ldg(reinterpret_cast<const uint32_t*>(x) + lane + 32 * i);
        float s = 0.f;
#pragma unroll
        for (int i = 0; i < 9; i++) s += bf_lo(xs[i]) + bf_hi(xs[i]);
#pragma unroll
        for (int o = 16; o; o >>= 1) s += __shfl_xor_sync(0xffffffffu, s, o);
        const float mean = s * (1.f / D_MODEL);
        float vs = 0.f;
#pragma unroll
        for (int i = 0; i < 9; i++) {
            float a = bf_lo(xs[i]) - mean, b = bf_hi(xs[i]) - mean;
            vs += a * a + b * b;
        }
#pragma unroll
        for (int o = 16; o; o >>= 1) vs += __shfl_xor_sync(0xffffffffu, vs, o);
        const float mb = bf16r(mean);
        const float den = bf16r(sqrtf(bf16r(bf16r(vs * (1.f / D_MODEL)) + 1e-5f)));
        uint32_t mine = xs[0];
#pragma unroll
        for (int i = 1; i < 9; i++) mine = (warp == i) ? xs[i] : mine;
        xn32[tid] = pack_bf16(bf16r(bf_lo(mine) - mb) / den, bf16r(bf_hi(mine) - mb) / den);
    }
    named_bar(6, NTHREADS);
    tag += 1;

    if (att && warp == 10) {
#pragma unroll 1
        for (int real = DRY ? 0 : 1; real < 2; real++) {
            if (real) {
                const unsigned long long* src = &g_q[(cta >> 3) * 256 + lane * 2];
                unsigned pend = 0xf;
                wait_item(QPOLL_AT, 100);
                for (int it = 0; pend && it < SPIN_LIMIT; it++) {
                    if (it) __nanosleep(200);
                    unsigned long long a[4], b[4];
#pragma unroll
                    for (int u = 0; u < 4; u++)
                        if (pend >> u & 1) ld_pkt2(src + u * 64, a[u], b[u]);
#pragma unroll
                    for (int u = 0; u < 4; u++)
                        if ((pend >> u & 1) && pkt_tag(a[u]) == tag && pkt_tag(b[u]) == tag) {
                            pend &= ~(1u << u);
                            reinterpret_cast<uint32_t*>(smem + OFF_Q)[u * 32 + lane] =
                                ((unsigned)a[u] >> 16) | ((unsigned)b[u] & 0xffff0000u);
                        }
                }
                __syncwarp();
                named_arrive(4, 32 * AW + 32);
                named_bar(5, 64);
                wait_item(item_of_w(POLL_AT), 100);
            }
            const int hb = cta & ~7, s = cta & 7;
            unsigned long long a[8], b[8];
            unsigned pend = (real && lane <= 16) ? (0xffu & ~(1u << s)) : 0u;
#pragma unroll
            for (int j = 0; j < 8; j++) a[j] = b[j] = 0ull;
            int it = 0;
            do {
                if (it) __nanosleep(100);
#pragma unroll
                for (int j = 0; j < 8; j++)
                    if (pend >> j & 1) ld_pkt2(&g_po[hb + j][s][lane * 2], a[j], b[j]);
#pragma unroll
                for (int j = 0; j < 8; j++)
                    if (pkt_tag(a[j]) == tag && pkt_tag(b[j]) == tag) pend &= ~(1u << j);
            } while (pend && ++it < SPIN_LIMIT);
            __syncwarp();
            {
                const float2 own = *reinterpret_cast<const float2*>(smem + OFF_OWN + (lane <= 16 ? lane : 0) * 8);
#pragma unroll
                for (int j = 0; j < 8; j++)
                    if (j == s) {
                        a[j] = __float_as_uint(own.x);
                        b[j] = __float_as_uint(own.y);
                    }
            }
            float M = -INFINITY;
#pragma unroll
            for (int j = 0; j < 8; j++) M = fmaxf(M, pkt_val(a[j]));
            float L = 0.f, sc[8];
#pragma unroll
            for (int j = 0; j < 8; j++) {
                sc[j] = ex2((pkt_val(a[j]) - M) * LOG2E);
                L = fmaf(pkt_val(b[j]), sc[j], L);
            }
            L = __shfl_sync(0xffffffffu, L, 16);
            float acc0 = 0.f, acc1 = 0.f;
#pragma unroll
            for (int j = 0; j < 8; j++) {
                const float w = __shfl_sync(0xffffffffu, sc[j], 16);
                acc0 = fmaf(pkt_val(a[j]), w, acc0);
                acc1 = fmaf(pkt_val(b[j]), w, acc1);
            }
            if (lane < 16) reinterpret_cast<uint32_t*>(smem + OFF_O)[lane] = pack_bf16(acc0 / L, acc1 / L);
            TRW(11);
        }
        __syncwarp();
        named_arrive(1, 320);
    }
    if (warp == 10) return;

    float res[4][4] = {};
    int real = (DRY && att && warp == 8) ? 0 : 1;
#pragma unroll 1
    for (int u = 0;;) {
        if (warp >= 4 && warp < 8) {
            const int fw = warp - 4;
            const uint32_t coff = ((fw * 48 + (mi >> 1) * 8 + lr) << 6) + (((mi & 1) ^ ((lr >> 1) & 3)) << 4);
            float s0 = 0.f, s1 = 0.f;
#pragma unroll 1
            for (int p = att ? -3 : 0; p < 6; p++) {
                const int pc = p < 0 ? p + 3 : p >> 1;
                uint32_t b[3][2];
#pragma unroll
                for (int ks = 0; ks < 3; ks++) {
                    b[ks][0] = xn32[pc * 96 + fw * 24 + ks * 8 + t];
                    b[ks][1] = xn32[pc * 96 + fw * 24 + ks * 8 + 4 + t];
                }
                const int sl = wait_item(p < 0 ? pc : att ? item_of_w(p) : XRING * u + p, 200);
                float acc[2][4] = {};
#pragma unroll
                for (int ks = 0; ks < 3; ks++)
#pragma unroll
                    for (int mt = 0; mt < 2; mt++) {
                        uint32_t a[4];
                        ldsm4t(sbase + sl * SLOT + ((coff + ks * 1024) ^ (mt << 5)), a);
                        mma16816(acc[mt], a, b[ks][0], b[ks][1]);
                    }
                if (lane == 0) mbar_arrive(empty0 + 8 * sl);
                const float val = (t & 2) ? ((t & 1) ? acc[1][2] : acc[1][0]) : ((t & 1) ? acc[0][2] : acc[0][0]);
                if (p >= 0 && (p & 1)) s1 += val; else s0 += val;
                if (p == -1 || p == 5) {
                    const int o = p < 0 ? 0 : 128;
                    red_s[o + fw * 32 + 8 * t + g] = s0;
                    red_s[256 + fw * 32 + 8 * t + g] = s1;
                    s0 = 0.f;
                    named_bar(3, 128);
                    if (p < 0 && warp == 4) {
                        st_pkt(&g_q[cta * 32 + lane],
                               pack_pkt(bf16r(red_s[lane] + red_s[32 + lane] + red_s[64 + lane] + red_s[96 + lane]), tag));
                        TRW(1);
                    }
                }
            }
        } else if (att && warp < AW) {
            named_bar(4, 32 * AW + 32);
            uint32_t qf[8][2];
            {
                const uint32_t* q32 = reinterpret_cast<const uint32_t*>(smem + OFF_Q) + (g & 1) * 64 + t;
#pragma unroll
                for (int ks = 0; ks < 8; ks++) {
                    qf[ks][0] = q32[ks * 8];
                    qf[ks][1] = q32[ks * 8 + 4];
                }
            }
            TR(3);
            const uint32_t koff = sbase + ((mi & 1) * 8 + lr) * 128 + (((mi >> 1) ^ lr) << 4);
            const uint32_t voff = sbase + ((mi >> 1) * 8 + lr) * 128 + (((mi & 1) ^ lr) << 4);
            float o[8][4] = {};
            float m0 = -INFINITY, m1 = -INFINITY, l0 = 0.f, l1 = 0.f;
            constexpr float SCALE = 0.08838834764831845f;
#pragma unroll 1
            for (int n = warp; n < NT; n += AW) {
                const int ik = item_of_tile(n);
                const int ks_ = wait_item(ik, 50);
                const uint32_t kaddr = koff + ks_ * SLOT;
                float sc[4][4] = {};
#pragma unroll
                for (int ks = 0; ks < 8; ks++) {
#pragma unroll
                    for (int i = 0; i < 4; i++) {
                        uint32_t a[4];
                        ldsm4((kaddr ^ ((ks & 3) << 5)) + (ks >> 2) * (SLOT / 2) + i * 2048, a);
                        mma16816(sc[i], a, qf[ks][0], qf[ks][1]);
                    }
                }
                if (lane == 0) mbar_arrive4(empty0 + 8 * ks_);
                float v[4];
#pragma unroll
                for (int j = 0; j < 4; j++) {
                    float a = (t & 1) ? sc[1][j] : sc[0][j];
                    float b = (t & 1) ? sc[3][j] : sc[2][j];
                    v[j] = bf16r(bf16r((t & 2) ? b : a) * SCALE);
                }
                float x0 = fmaxf(v[0], v[2]), x1 = fmaxf(v[1], v[3]);
#pragma unroll
                for (int off = 4; off <= 16; off <<= 1) {
                    x0 = fmaxf(x0, __shfl_xor_sync(0xffffffffu, x0, off));
                    x1 = fmaxf(x1, __shfl_xor_sync(0xffffffffu, x1, off));
                }
                const float n0 = fmaxf(m0, x0), n1 = fmaxf(m1, x1);
                const float a0 = ex2((m0 - n0) * LOG2E), a1 = ex2((m1 - n1) * LOG2E);
                m0 = n0;
                m1 = n1;
                const float p0 = ex2((v[0] - n0) * LOG2E), p1 = ex2((v[1] - n1) * LOG2E);
                const float p2 = ex2((v[2] - n0) * LOG2E), p3 = ex2((v[3] - n1) * LOG2E);
                l0 = fmaf(l0, a0, p0 + p2);
                l1 = fmaf(l1, a1, p1 + p3);
                const uint32_t blo = movmat(pack_bf16(p0, p1));
                const uint32_t bhi = movmat(pack_bf16(p2, p3));
#pragma unroll
                for (int i = 0; i < 8; i++) {
                    o[i][0] *= a0;
                    o[i][1] *= a1;
                    o[i][2] *= a0;
                    o[i][3] *= a1;
                }
                const int vs_ = wait_item(ik + KG, 50);
                const uint32_t vaddr = voff + vs_ * SLOT;
#pragma unroll
                for (int i = 0; i < 4; i++) {
                    const uint32_t b0 = ((g >> 1) == i) ? blo : 0u, b1 = ((g >> 1) == i) ? bhi : 0u;
#pragma unroll
                    for (int md = 0; md < 8; md++) {
                        uint32_t a[4];
                        ldsm4t((vaddr ^ ((md & 3) << 5)) + (md >> 2) * (SLOT / 2) + i * 2048, a);
                        mma16816(o[md], a, b0, b1);
                    }
                }
                if (lane == 0) mbar_arrive4(empty0 + 8 * vs_);
            }
            TR(4);
            float w0 = m0, w1 = m1;
#pragma unroll
            for (int off = 1; off <= 2; off <<= 1) {
                w0 = fmaxf(w0, __shfl_xor_sync(0xffffffffu, w0, off));
                w1 = fmaxf(w1, __shfl_xor_sync(0xffffffffu, w1, off));
            }
            const float s0 = ex2((m0 - w0) * LOG2E), s1 = ex2((m1 - w1) * LOG2E);
            l0 *= s0;
            l1 *= s1;
#pragma unroll
            for (int off = 1; off <= 16; off <<= 1) {
                l0 += __shfl_xor_sync(0xffffffffu, l0, off);
                l1 += __shfl_xor_sync(0xffffffffu, l1, off);
            }
            float* mo = reinterpret_cast<float*>(smem + OFF_MO);
            float* ml = reinterpret_cast<float*>(smem + OFF_ML);
#pragma unroll
            for (int md = 0; md < 8; md++) {
                float a = o[md][0] * s0, b = o[md][1] * s1, c = o[md][2] * s0, d = o[md][3] * s1;
                const bool u1 = t & 1, u2 = t & 2;
                float k0 = u2 ? c : a, k1 = u2 ? d : b, e0 = u2 ? a : c, e1 = u2 ? b : d;
                k0 += __shfl_xor_sync(0xffffffffu, e0, 2);
                k1 += __shfl_xor_sync(0xffffffffu, e1, 2);
                float k = u1 ? k1 : k0, e = u1 ? k0 : k1;
                k += __shfl_xor_sync(0xffffffffu, e, 1);
                mo[warp * 256 + (t & 1) * 128 + md * 16 + g + (t >> 1) * 8] = k;
            }
            if (lane == 0) {
                ml[warp * 4 + 0] = w0; ml[warp * 4 + 1] = l0; ml[warp * 4 + 2] = w1; ml[warp * 4 + 3] = l1;
            }
            named_bar(7, 32 * AW);
#pragma unroll 1
            for (int sl = warp; sl < 8; sl += AW) {
                const int hsel = sl >> 2;
                float M = -INFINITY;
#pragma unroll
                for (int w = 0; w < AW; w++) M = fmaxf(M, ml[w * 4 + hsel * 2]);
                float acc = 0.f, L = 0.f;
#pragma unroll
                for (int w = 0; w < AW; w++) {
                    const float sc = ex2((ml[w * 4 + hsel * 2] - M) * LOG2E);
                    acc = fmaf(mo[w * 256 + sl * 32 + lane], sc, acc);
                    L = fmaf(ml[w * 4 + hsel * 2 + 1], sc, L);
                }
                if (sl != (cta & 7)) {
                    st_pkt(&g_po[cta][sl][lane], pack_pkt(acc, tag));
                    if (lane < 8) st_pkt2(&g_po[cta][sl][32 + 2 * lane], pack_pkt(M, tag), pack_pkt(L, tag));
                } else {
                    float* own = reinterpret_cast<float*>(smem + OFF_OWN);
                    own[lane] = acc;
                    if (lane == 0) { own[32] = M; own[33] = L; }
                    named_arrive(5, 64);
                }
            }
            TR(5);
        }
        if (warp == 4 || !real) {
            const float gv = bf16r(red_s[128 + lane] + red_s[160 + lane] + red_s[192 + lane] + red_s[224 + lane]);
            const float uv = bf16r(red_s[256 + lane] + red_s[288 + lane] + red_s[320 + lane] + red_s[352 + lane]);
            const float sg = bf16r(gv / (1.f + __expf(-gv)));
            if (real) reinterpret_cast<__nv_bfloat16*>(smem + OFF_H)[lane] = __float2bfloat16_rn(sg * uv);
            if (real) TRW(2);
        }
        const uint32_t roff = ((lr * 9 + warp) << 7) + (((mi & 1) ^ ((lr + warp) & 7)) << 4);
#pragma unroll 1
        for (int k = 0; k < (att ? 4 : 2); k++) {
            int s0 = 0, s1 = 0;
            if (real) {
                if (k == 0) named_bar(2, 288);
                if (k == 2) named_bar(1, 320);
                const int item = (att ? item_of_w(6) : XRING * u + 6) + 2 * k;
                s0 = wait_item(item, 20);
                s1 = wait_item(item + 1, 20);
            }
            const uint32_t base = sbase + ((mi >> 1) ? s1 : s0) * SLOT;
            const uint32_t* v32 = reinterpret_cast<const uint32_t*>(smem + OFF_H) + 8 * k;
            const uint32_t b0 = v32[t], b1 = v32[4 + t];
#pragma unroll
            for (int mt = 0; mt < 4; mt++) {
                uint32_t a[4];
                ldsm4t(base + (roff ^ (mt << 5)), a);
                mma16816(res[mt], a, b0, b1);
            }
        }
        if (!att) {
            named_bar(2, 288);
            if (tid < 4) mbar_arrive4(empty0 + 8 * (6 + tid));
            if (++u < 4) continue;
        }
        const float r0 = (t & 2) ? ((t & 1) ? res[3][0] : res[2][0]) : ((t & 1) ? res[1][0] : res[0][0]);
        const float r1 = (t & 2) ? ((t & 1) ? res[3][2] : res[2][2]) : ((t & 1) ? res[1][2] : res[0][2]);
        if (real) {
            asm volatile("red.relaxed.gpu.global.add.v4.f32 [%0], {%1, %2, %3, %4};"
                         ::"l"(&g_acc[cta % NCOPY][tid]), "f"(r0), "f"(r1), "f"(1.0f), "f"(0.0f) : "memory");
            break;
        }
        real = 1;
#pragma unroll
        for (int mt = 0; mt < 4; mt++) res[mt][0] = res[mt][1] = res[mt][2] = res[mt][3] = 0.f;
    }
    TR(8);

    if (!att) {
        const int slot = (cta - ATT_CTAS) * 72 + (tid >> 2), copy = tid & 3;
        const int col = (slot >> 5) * 64 + (slot & 3) * 16 + ((slot & 31) >> 2) + (copy & 1) * 8;
        float4* src = &g_acc[copy][slot];
        const float xv = __bfloat162float(x[col]);
#pragma unroll 1
        for (int fin = DRY ? 0 : 1; fin < 2; fin++) {
            unsigned long long a = 0, b = 0;
            if (fin) {
                if (warp == 0) {
#pragma unroll 1
                    for (int it = 0; it < SPIN_LIMIT; it++) {
                        float cnt = 0.f;
                        if (lane < 4) {
                            ld_pkt2(reinterpret_cast<const unsigned long long*>(src), a, b);
                            cnt = pkt_val(b);
                        }
                        cnt += __shfl_xor_sync(0xffffffffu, cnt, 1);
                        cnt += __shfl_xor_sync(0xffffffffu, cnt, 2);
                        cnt = __shfl_sync(0xffffffffu, cnt, 0);
                        if (cnt >= (float)(NCTA - FIN_X)) break;
                        __nanosleep(cnt > 8.f ? 100 : 300);
                    }
                }
                named_bar(2, 288);
#pragma unroll 1
                for (int it = 0; it < SPIN_LIMIT; it++) {
                    ld_pkt2(reinterpret_cast<const unsigned long long*>(src), a, b);
                    if (pkt_val(b) == (float)(NCTA / NCOPY)) break;
                }
            }
            __syncwarp();
            const float s0 = pkt_val(a), s1 = __uint_as_float(pkt_tag(a));
            float k = (copy & 1) ? s1 : s0;
            k += __shfl_xor_sync(0xffffffffu, (copy & 1) ? s0 : s1, 1);
            k += __shfl_xor_sync(0xffffffffu, k, 2);
            if (fin) {
                if (copy < 2) out[col] = __float2bfloat16_rn(xv + k);
                *src = make_float4(0.f, 0.f, 0.f, 0.f);
                if (cta == ATT_CTAS && tid == 0) g_epoch = tag;
            }
        }
    }
    TR(9);
}

typedef CUresult (*EncodeFn)(CUtensorMap*, CUtensorMapDataType, cuuint32_t, void*, const cuuint64_t*, const cuuint64_t*,
                             const cuuint32_t*, const cuuint32_t*, CUtensorMapInterleave, CUtensorMapSwizzle,
                             CUtensorMapL2promotion, CUtensorMapFloatOOBfill);

void make_map(EncodeFn enc, CUtensorMap* m, void* base, uint64_t cols, uint64_t rows, uint32_t bc, uint32_t br,
              CUtensorMapSwizzle sw) {
    cuuint64_t gd[2] = {cols, rows};
    cuuint64_t gs[1] = {cols * 2};
    cuuint32_t bx[2] = {bc, br};
    cuuint32_t es[2] = {1, 1};
    enc(m, CU_TENSOR_MAP_DATA_TYPE_BFLOAT16, 2, base, gd, gs, bx, es, CU_TENSOR_MAP_INTERLEAVE_NONE, sw,
        CU_TENSOR_MAP_L2_PROMOTION_L2_256B, CU_TENSOR_MAP_FLOAT_OOB_FILL_NONE);
}

}

extern "C" void kernel_launch(void* const* d_in, const int* in_sizes, int n_in, void* d_out, int out_size) {
    (void)in_sizes; (void)n_in; (void)out_size;
    static EncodeFn enc = nullptr;
    static unsigned tau = 666;
    if (!enc) {
        int dev = 0, khz = 0, bits = 0;
        cudaGetDevice(&dev);
        if (cudaDeviceGetAttribute(&khz, cudaDevAttrMemoryClockRate, dev) == cudaSuccess &&
            cudaDeviceGetAttribute(&bits, cudaDevAttrGlobalMemoryBusWidth, dev) == cudaSuccess && khz > 0 && bits > 0)
            tau = (unsigned)(ATT_CTAS * 16384.0 / (BW_EFF * 2.0 * khz * 1e-6 * (bits / 8)) + 0.5);
        void* fn = nullptr;
        cudaDriverEntryPointQueryResult qr;
        cudaGetDriverEntryPoint("cuTensorMapEncodeTiled", &fn, cudaEnableDefault, &qr);
        enc = (EncodeFn)fn;
        cudaFuncSetAttribute(fused_decode_kernel, cudaFuncAttributeMaxDynamicSharedMemorySize, SMEM_BYTES);
    }
    Maps maps;
    make_map(enc, &maps.k, d_in[1], 128, 16 * 16384, 64, TP, CU_TENSOR_MAP_SWIZZLE_128B);
    make_map(enc, &maps.v, d_in[2], 128, 16 * 16384, 64, TP, CU_TENSOR_MAP_SWIZZLE_128B);
    make_map(enc, &maps.wq, d_in[3], NQ, D_MODEL, 32, 192, CU_TENSOR_MAP_SWIZZLE_64B);
    make_map(enc, &maps.wg, d_in[6], FF, D_MODEL, 32, 192, CU_TENSOR_MAP_SWIZZLE_64B);
    make_map(enc, &maps.wu, d_in[7], FF, D_MODEL, 32, 192, CU_TENSOR_MAP_SWIZZLE_64B);
    make_map(enc, &maps.wd, d_in[8], 64, FF * 9, 64, 72, CU_TENSOR_MAP_SWIZZLE_128B);
    make_map(enc, &maps.wo, d_in[4], 64, NQ * 9, 64, 72, CU_TENSOR_MAP_SWIZZLE_128B);
    fused_decode_kernel<<<NCTA, NTHREADS, SMEM_BYTES>>>(maps, (const __nv_bfloat16*)d_in[0], (__nv_bfloat16*)d_out, tau);
}
```

```cpp
#include <cuda_runtime.h>
#include <cuda.h>
#include <cuda_bf16.h>
#include <stdint.h>

namespace {

constexpr int D_MODEL = 576;
constexpr int NQ = 4096;
constexpr int FF = 4608;

constexpr int NCTA = 132;
constexpr int ATT_CTAS = 128;
constexpr int NTHREADS = 352;

constexpr int AW = 4;
constexpr int TP = 64;
constexpr int NT = 2048 / TP;
constexpr int SLOT = TP * 256;
constexpr int NSLOT = 13;
constexpr int CPB = 192 * 64;
constexpr int RPB = 8 * 1152;

#define DEPTH 6
#define TDEPTH 5
#define BW_EFF 0.9394
#define T_OFF 500
#define XSLOW 10
#define POLL_AT 5
#define QPOLL_AT 6
#define FIN_X 110
constexpr int KG = 4;

constexpr int IT_KV = 3, IT_W = IT_KV + 2 * NT, IT_END = IT_W + 14, XRING = 10;
static_assert(NT % KG == 0 && POLL_AT >= 1, "");
__device__ constexpr int item_of_tile(int n) { return IT_KV + 2 * (n - n % KG) + n % KG; }
__device__ constexpr int item_of_w(int j) { return IT_W + j; }

constexpr int OFF_RED = NSLOT * SLOT;
constexpr int OFF_XN = OFF_RED + 3 * 4 * 32 * 4;
constexpr int OFF_Q = OFF_XN + D_MODEL * 2;
constexpr int OFF_H = OFF_Q + 512;
constexpr int OFF_O = OFF_H + 64;
constexpr int OFF_OWN = OFF_O + 64;
constexpr int OFF_MO = OFF_OWN + 144;
constexpr int OFF_ML = OFF_MO + AW * 256 * 4;
constexpr int OFF_BAR = OFF_ML + AW * 16;
constexpr int OFF_ISSUED = OFF_BAR + 2 * NSLOT * 8;
constexpr int SMEM_BYTES = OFF_ISSUED + 16 + 1024;
static_assert(SMEM_BYTES <= 232448, "smem");

constexpr int NCOPY = 4;
constexpr int SPIN_LIMIT = 1 << 17;
constexpr int WAIT_LIMIT = 1 << 17;
constexpr float LOG2E = 1.4426950408889634f;

__device__ unsigned g_epoch;
__device__ __align__(128) unsigned long long g_q[NQ];
__device__ __align__(128) unsigned long long g_po[ATT_CTAS][8][48];
__device__ __align__(128) float4 g_acc[NCOPY][288];

__device__ __forceinline__ uint32_t smem_u32(const void* p) { return (uint32_t)__cvta_generic_to_shared(p); }
__device__ __forceinline__ void mbar_init(uint32_t bar, uint32_t cnt) {
    asm volatile("mbarrier.init.shared::cta.b64 [%0], %1;" ::"r"(bar), "r"(cnt) : "memory");
}
__device__ __forceinline__ void mbar_expect_tx(uint32_t bar, uint32_t bytes) {
    asm volatile("mbarrier.arrive.expect_tx.shared::cta.b64 _, [%0], %1;" ::"r"(bar), "r"(bytes) : "memory");
}
__device__ __forceinline__ void mbar_arrive(uint32_t bar) {
    asm volatile("mbarrier.arrive.shared::cta.b64 _, [%0];" ::"r"(bar) : "memory");
}
__device__ __forceinline__ void mbar_arrive4(uint32_t bar) {
    asm volatile("mbarrier.arrive.shared::cta.b64 _, [%0], 4;" ::"r"(bar) : "memory");
}
__device__ __forceinline__ void mbar_wait(uint32_t bar, uint32_t parity) {
    for (int it = 0; it < WAIT_LIMIT; it++) {
        uint32_t ok;
        asm volatile(
            "{\n.reg .pred p;\n"
            "mbarrier.try_wait.parity.shared::cta.b64 p, [%1], %2, %3;\n"
            "selp.u32 %0, 1, 0, p;\n}\n"
            : "=r"(ok) : "r"(bar), "r"(parity), "r"(1000) : "memory");
        if (ok) break;
    }
}
__device__ __forceinline__ void mbar_spin(uint32_t bar, uint32_t parity) {
    for (int it = 0; it < (1 << 22); it++) {
        uint32_t ok;
        asm volatile(
            "{\n.reg .pred p;\n"
            "mbarrier.test_wait.parity.shared::cta.b64 p, [%1], %2;\n"
            "selp.u32 %0, 1, 0, p;\n}\n"
            : "=r"(ok) : "r"(bar), "r"(parity) : "memory");
        if (ok) break;
    }
}
__device__ __forceinline__ unsigned long long gtime() {
    unsigned long long t;
    asm volatile("mov.u64 %0, %globaltimer;" : "=l"(t));
    return t;
}
__device__ __forceinline__ void tma2d(uint32_t dst, const CUtensorMap* map, int c0, int c1, uint32_t bar, uint64_t pol) {
    asm volatile(
        "cp.async.bulk.tensor.2d.shared::cluster.global.mbarrier::complete_tx::bytes.L2::cache_hint "
        "[%0], [%1, {%3, %4}], [%2], %5;"
        ::"r"(dst), "l"(map), "r"(bar), "r"(c0), "r"(c1), "l"(pol) : "memory");
}
__device__ __forceinline__ unsigned long long pack_pkt(float v, unsigned tag) {
    return (unsigned long long)__float_as_uint(v) | ((unsigned long long)tag << 32);
}
__device__ __forceinline__ void st_pkt(unsigned long long* p, unsigned long long v) {
    asm volatile("st.relaxed.gpu.global.b64 [%0], %1;" ::"l"(p), "l"(v) : "memory");
}
__device__ __forceinline__ void st_pkt2(unsigned long long* p, unsigned long long a, unsigned long long b) {
    asm volatile("st.relaxed.gpu.global.v2.b64 [%0], {%1, %2};" ::"l"(p), "l"(a), "l"(b) : "memory");
}
__device__ __forceinline__ void ld_pkt2(const unsigned long long* p, unsigned long long& a, unsigned long long& b) {
    asm volatile("ld.relaxed.gpu.global.v2.b64 {%0, %1}, [%2];" : "=l"(a), "=l"(b) : "l"(p) : "memory");
}
__device__ __forceinline__ float pkt_val(unsigned long long v) { return __uint_as_float((unsigned)v); }
__device__ __forceinline__ unsigned pkt_tag(unsigned long long v) { return (unsigned)(v >> 32); }

__device__ __forceinline__ float bf16r(float v) { return __bfloat162float(__float2bfloat16_rn(v)); }
__device__ __forceinline__ float bf_lo(uint32_t v) { return __uint_as_float(v << 16); }
__device__ __forceinline__ float bf_hi(uint32_t v) { return __uint_as_float(v & 0xffff0000u); }
__device__ __forceinline__ uint32_t pack_bf16(float lo, float hi) {
    uint32_t r;
    asm("cvt.rn.bf16x2.f32 %0, %1, %2;" : "=r"(r) : "f"(hi), "f"(lo));
    return r;
}
__device__ __forceinline__ float ex2(float x) {
    float r;
    asm("ex2.approx.ftz.f32 %0, %1;" : "=f"(r) : "f"(x));
    return r;
}
__device__ __forceinline__ void ldsm4(uint32_t addr, uint32_t (&r)[4]) {
    asm volatile("ldmatrix.sync.aligned.m8n8.x4.shared.b16 {%0,%1,%2,%3}, [%4];"
                 : "=r"(r[0]), "=r"(r[1]), "=r"(r[2]), "=r"(r[3]) : "r"(addr) : "memory");
}
__device__ __forceinline__ void ldsm4t(uint32_t addr, uint32_t (&r)[4]) {
    asm volatile("ldmatrix.sync.aligned.m8n8.x4.trans.shared.b16 {%0,%1,%2,%3}, [%4];"
                 : "=r"(r[0]), "=r"(r[1]), "=r"(r[2]), "=r"(r[3]) : "r"(addr) : "memory");
}
__device__ __forceinline__ void mma16816(float (&c)[4], const uint32_t (&a)[4], uint32_t b0, uint32_t b1) {
    asm volatile(
        "mma.sync.aligned.m16n8k16.row.col.f32.bf16.bf16.f32 {%0,%1,%2,%3}, {%4,%5,%6,%7}, {%8,%9}, {%0,%1,%2,%3};"
        : "+f"(c[0]), "+f"(c[1]), "+f"(c[2]), "+f"(c[3])
        : "r"(a[0]), "r"(a[1]), "r"(a[2]), "r"(a[3]), "r"(b0), "r"(b1));
}
__device__ __forceinline__ uint32_t movmat(uint32_t a) {
    uint32_t d;
    asm volatile("movmatrix.sync.aligned.m8n8.trans.b16 %0, %1;" : "=r"(d) : "r"(a));
    return d;
}
__device__ __forceinline__ void named_bar(int id, int n) {
    asm volatile("bar.sync %0, %1;" ::"r"(id), "r"(n) : "memory");
}
__device__ __forceinline__ void named_arrive(int id, int n) {
    asm volatile("bar.arrive %0, %1;" ::"r"(id), "r"(n) : "memory");
}

struct Maps {
    CUtensorMap k, v, wq, wg, wu, wd, wo;
};

__global__ void __launch_bounds__(NTHREADS, 1)
fused_decode_kernel(const __grid_constant__ Maps maps, const __nv_bfloat16* __restrict__ x,
                    __nv_bfloat16* __restrict__ out, const unsigned tau) {
    extern __shared__ unsigned char smem_raw[];
    const uint32_t sbase = (smem_u32(smem_raw) + 1023u) & ~1023u;
    const uint32_t full0 = sbase + OFF_BAR, empty0 = full0 + 8 * NSLOT;
    const int tid = threadIdx.x, cta = blockIdx.x;
    const bool att = cta < ATT_CTAS;
    unsigned char* smem = smem_raw + (sbase - smem_u32(smem_raw));
    volatile int* issued_s = reinterpret_cast<volatile int*>(smem + OFF_ISSUED);
    const int ring = att ? NSLOT : XRING;
    if (tid >= 288 && tid < 320) {
        if (tid != 288) asm volatile("exit;");
        const unsigned t0 = (unsigned)gtime();
        uint64_t pol, polw;
#pragma unroll
        for (int b = 0; b < 3; b++) mbar_init(full0 + 8 * b, 1);
        asm volatile("fence.mbarrier_init.release.cluster;" ::: "memory");
        asm volatile("createpolicy.fractional.L2::evict_normal.b64 %0, 1.0;" : "=l"(polw));
        int unit = att ? cta : ATT_CTAS + (cta - ATT_CTAS) * 4;
#pragma unroll
        for (int b = 0; b < 3; b++) {
            mbar_expect_tx(full0 + 8 * b, CPB);
            tma2d(sbase + b * SLOT, att ? &maps.wq : (b & 1) ? &maps.wu : &maps.wg, unit * 32, (att ? b : b >> 1) * 192,
                  full0 + 8 * b, polw);
        }
#pragma unroll 1
        for (int i = 0; i < 7; i++) asm volatile("prefetch.tensormap [%0];" ::"l"(&maps.k + i) : "memory");
#pragma unroll 1
        for (int i = 3; i < 2 * NSLOT; i++) mbar_init(full0 + 8 * i, i < NSLOT ? 1 : 4);
        *issued_s = 3;
        asm volatile("fence.mbarrier_init.release.cluster;" ::: "memory");
        named_arrive(6, NTHREADS);
        asm volatile("createpolicy.fractional.L2::evict_first.b64 %0, 1.0;" : "=l"(pol));
        const int nitems = att ? IT_END : 4 * XRING;
        int slot = 3, ph = 0, lslot = 0, lph = 0, landed = 0, depth = DEPTH;
        unsigned due = T_OFF << 4;
        int n = att ? 0 : NT, half = 0, j = att ? 0 : 3;
#pragma unroll 1
        for (int i = 3; i < nitems; i++) {
            if (!att && j == XRING) { j = 0; unit++; }
            const uint32_t bar = full0 + 8 * slot, dst = sbase + slot * SLOT;
            if (i >= ring) mbar_wait(empty0 + 8 * slot, ph ^ 1);
            while (landed <= i - depth) {
                mbar_wait(full0 + 8 * lslot, lph);
                landed++;
                if (++lslot == ring) { lslot = 0; lph ^= 1; }
            }
            if (n < NT || !att)
                for (int it = 0; (int)((unsigned)gtime() - t0 - (due >> 4)) < 0 && it < (1 << 22); it++) {}
            uint32_t bytes;
            if (n < NT) {
                const CUtensorMap* m = half >= KG ? &maps.v : &maps.k;
                const int row = cta * 2048 + (n + (half >= KG ? half - KG : half)) * TP;
                bytes = SLOT;
                mbar_expect_tx(bar, SLOT);
                tma2d(dst, m, 0, row, bar, pol);
                tma2d(dst + SLOT / 2, m, 64, row, bar, pol);
                if (++half == 2 * KG) { half = 0; n += KG; }
            } else if (j < 6) {
                const CUtensorMap* m = (j & 1) ? &maps.wu : &maps.wg;
                bytes = CPB;
                mbar_expect_tx(bar, CPB);
                tma2d(dst, m, unit * 32, (j >> 1) * 192, bar, polw);
                j++;
            } else {
                bytes = RPB;
                mbar_expect_tx(bar, RPB);
                tma2d(dst, j < 10 ? &maps.wd : &maps.wo, 0, unit * 288 + ((j - 6) & 3) * 72, bar, pol);
                j++;
            }
            due += (bytes >> 10) * (att ? tau : tau * XSLOW / 4);
            *issued_s = i + 1;
            if (n == NT) depth = TDEPTH;
            if (++slot == ring) { slot = 0; ph ^= 1; }
        }
        asm volatile("exit;");
    }
    const int lane = tid & 31;
    const int warp = __shfl_sync(0xffffffffu, tid >> 5, 0);
    float* red_s = reinterpret_cast<float*>(smem + OFF_RED);
    uint32_t* xn32 = reinterpret_cast<uint32_t*>(smem + OFF_XN);
    const int g = lane >> 2, t = lane & 3;
    const int lr = lane & 7, mi = lane >> 3;

    auto wait_item = [&](int i, int sleep_ns) {
        for (int it = 0; *issued_s <= i && it < SPIN_LIMIT; it++) __nanosleep(sleep_ns);
        const int q = att ? i / NSLOT : i / XRING, sl = i - q * ring;
        mbar_wait(full0 + 8 * sl, q & 1);
        __syncwarp();
        return sl;
    };

    unsigned tag = 0;
    asm volatile("ld.relaxed.gpu.global.u32 %0, [%1];" : "=r"(tag) : "l"(&g_epoch) : "memory");
    if (warp < 9) {
        uint32_t xs[9];
#pragma unroll
        for (int i = 0; i < 9; i++) xs[i] = __ldg(reinterpret_cast<const uint32_t*>(x) + lane + 32 * i);
        float s = 0.f;
#pragma unroll
        for (int i = 0; i < 9; i++) s += bf_lo(xs[i]) + bf_hi(xs[i]);
#pragma unroll
        for (int o = 16; o; o >>= 1) s += __shfl_xor_sync(0xffffffffu, s, o);
        const float mean = s * (1.f / D_MODEL);
        float vs = 0.f;
#pragma unroll
        for (int i = 0; i < 9; i++) {
            float a = bf_lo(xs[i]) - mean, b = bf_hi(xs[i]) - mean;
            vs += a * a + b * b;
        }
#pragma unroll
        for (int o = 16; o; o >>= 1) vs += __shfl_xor_sync(0xffffffffu, vs, o);
        const float mb = bf16r(mean);
        const float den = bf16r(sqrtf(bf16r(bf16r(vs * (1.f / D_MODEL)) + 1e-5f)));
        uint32_t mine = xs[0];
#pragma unroll
        for (int i = 1; i < 9; i++) mine = (warp == i) ? xs[i] : mine;
        xn32[tid] = pack_bf16(bf16r(bf_lo(mine) - mb) / den, bf16r(bf_hi(mine) - mb) / den);
    }
    named_bar(6, NTHREADS);
    tag += 1;

    if (warp == 10) {
        if (!att) return;
        {
            const unsigned long long* src = &g_q[(cta >> 3) * 256 + lane * 2];
            unsigned pend = 0xf;
            wait_item(QPOLL_AT, 100);
            for (int it = 0; pend && it < SPIN_LIMIT; it++) {
                if (it) __nanosleep(200);
                unsigned long long a[4], b[4];
#pragma unroll
                for (int u = 0; u < 4; u++)
                    if (pend >> u & 1) ld_pkt2(src + u * 64, a[u], b[u]);
#pragma unroll
                for (int u = 0; u < 4; u++)
                    if ((pend >> u & 1) && pkt_tag(a[u]) == tag && pkt_tag(b[u]) == tag) {
                        pend &= ~(1u << u);
                        reinterpret_cast<uint32_t*>(smem + OFF_Q)[u * 32 + lane] =
                            ((unsigned)a[u] >> 16) | ((unsigned)b[u] & 0xffff0000u);
                    }
            }
            __syncwarp();
            named_arrive(4, 32 * AW + 32);
        }
        named_bar(5, 64);
        wait_item(item_of_w(POLL_AT), 100);
        const int hb = cta & ~7, s = cta & 7;
        unsigned long long a[8], b[8];
        unsigned pend = lane <= 16 ? (0xffu & ~(1u << s)) : 0u;
#pragma unroll
        for (int j = 0; j < 8; j++) a[j] = b[j] = 0ull;
        for (int it = 0; pend && it < SPIN_LIMIT; it++) {
            if (it) __nanosleep(100);
#pragma unroll
            for (int j = 0; j < 8; j++)
                if (pend >> j & 1) ld_pkt2(&g_po[hb + j][s][lane * 2], a[j], b[j]);
#pragma unroll
            for (int j = 0; j < 8; j++)
                if (pkt_tag(a[j]) == tag && pkt_tag(b[j]) == tag) pend &= ~(1u << j);
        }
        __syncwarp();
        const float2 own = *reinterpret_cast<const float2*>(smem + OFF_OWN + (lane <= 16 ? lane : 0) * 8);
#pragma unroll
        for (int j = 0; j < 8; j++)
            if (j == s) {
                a[j] = __float_as_uint(own.x);
                b[j] = __float_as_uint(own.y);
            }
        float M = -INFINITY;
#pragma unroll
        for (int j = 0; j < 8; j++) M = fmaxf(M, pkt_val(a[j]));
        float L = 0.f, sc[8];
#pragma unroll
        for (int j = 0; j < 8; j++) {
            sc[j] = ex2((pkt_val(a[j]) - M) * LOG2E);
            L = fmaf(pkt_val(b[j]), sc[j], L);
        }
        L = __shfl_sync(0xffffffffu, L, 16);
        float acc0 = 0.f, acc1 = 0.f;
#pragma unroll
        for (int j = 0; j < 8; j++) {
            const float w = __shfl_sync(0xffffffffu, sc[j], 16);
            acc0 = fmaf(pkt_val(a[j]), w, acc0);
            acc1 = fmaf(pkt_val(b[j]), w, acc1);
        }
        if (lane < 16) reinterpret_cast<uint32_t*>(smem + OFF_O)[lane] = pack_bf16(acc0 / L, acc1 / L);
        __syncwarp();
        named_arrive(1, 320);
        return;
    }

    float res[4][4] = {};
    float4* accp = &g_acc[cta % NCOPY][warp * 32 + t * 8 + g];
    asm volatile("" : "+l"(accp));
#pragma unroll 1
    for (int u = 0;;) {
        if (warp >= 4 && warp < 8) {
            const int fw = warp - 4;
            const uint32_t coff = ((fw * 48 + (mi >> 1) * 8 + lr) << 6) + (((mi & 1) ^ ((lr >> 1) & 3)) << 4);
            float s0 = 0.f, s1 = 0.f;
#pragma unroll 1
            for (int p = att ? -3 : 0; p < 6; p++) {
                const int pc = p < 0 ? p + 3 : p >> 1;
                uint32_t b[3][2];
#pragma unroll
                for (int ks = 0; ks < 3; ks++) {
                    b[ks][0] = xn32[pc * 96 + fw * 24 + ks * 8 + t];
                    b[ks][1] = xn32[pc * 96 + fw * 24 + ks * 8 + 4 + t];
                }
                const int sl = wait_item(p < 0 ? pc : att ? item_of_w(p) : XRING * u + p, 200);
                float acc[2][4] = {};
#pragma unroll
                for (int ks = 0; ks < 3; ks++)
#pragma unroll
                    for (int mt = 0; mt < 2; mt++) {
                        uint32_t a[4];
                        ldsm4t(sbase + sl * SLOT + ((coff + ks * 1024) ^ (mt << 5)), a);
                        mma16816(acc[mt], a, b[ks][0], b[ks][1]);
                    }
                if (lane == 0) mbar_arrive(empty0 + 8 * sl);
                const float val = (t & 2) ? ((t & 1) ? acc[1][2] : acc[1][0]) : ((t & 1) ? acc[0][2] : acc[0][0]);
                if (p >= 0 && (p & 1)) s1 += val; else s0 += val;
                if (p == -1 || p == 5) {
                    const int o = p < 0 ? 0 : 128;
                    red_s[o + fw * 32 + 8 * t + g] = s0;
                    red_s[256 + fw * 32 + 8 * t + g] = s1;
                    s0 = 0.f;
                    named_bar(3, 128);
                    if (p < 0 && warp == 4) {
                        st_pkt(&g_q[cta * 32 + lane],
                               pack_pkt(bf16r(red_s[lane] + red_s[32 + lane] + red_s[64 + lane] + red_s[96 + lane]), tag));
                    }
                }
            }
        } else if (att && warp < AW) {
            named_bar(4, 32 * AW + 32);
            uint32_t qf[8][2];
            {
                const uint32_t* q32 = reinterpret_cast<const uint32_t*>(smem + OFF_Q) + (g & 1) * 64 + t;
#pragma unroll
                for (int ks = 0; ks < 8; ks++) {
                    qf[ks][0] = q32[ks * 8];
                    qf[ks][1] = q32[ks * 8 + 4];
                }
            }
            const uint32_t koff = sbase + ((mi & 1) * 8 + lr) * 128 + (((mi >> 1) ^ lr) << 4);
            const uint32_t voff = sbase + ((mi >> 1) * 8 + lr) * 128 + (((mi & 1) ^ lr) << 4);
            float o[8][4] = {};
            float m0 = -INFINITY, m1 = -INFINITY, l0 = 0.f, l1 = 0.f;
            constexpr float SCALE = 0.08838834764831845f;
#pragma unroll 1
            for (int n = warp; n < NT; n += AW) {
                const int ik = item_of_tile(n);
                const int ks_ = wait_item(ik, 50);
                const uint32_t kaddr = koff + ks_ * SLOT;
                float sc[4][4] = {};
#pragma unroll
                for (int ks = 0; ks < 8; ks++) {
#pragma unroll
                    for (int i = 0; i < 4; i++) {
                        uint32_t a[4];
                        ldsm4((kaddr ^ ((ks & 3) << 5)) + (ks >> 2) * (SLOT / 2) + i * 2048, a);
                        mma16816(sc[i], a, qf[ks][0], qf[ks][1]);
                    }
                }
                if (lane == 0) mbar_arrive4(empty0 + 8 * ks_);
                float v[4];
#pragma unroll
                for (int j = 0; j < 4; j++) {
                    float a = (t & 1) ? sc[1][j] : sc[0][j];
                    float b = (t & 1) ? sc[3][j] : sc[2][j];
                    v[j] = bf16r(bf16r((t & 2) ? b : a) * SCALE);
                }
                float x0 = fmaxf(v[0], v[2]), x1 = fmaxf(v[1], v[3]);
#pragma unroll
                for (int off = 4; off <= 16; off <<= 1) {
                    x0 = fmaxf(x0, __shfl_xor_sync(0xffffffffu, x0, off));
                    x1 = fmaxf(x1, __shfl_xor_sync(0xffffffffu, x1, off));
                }
                const float n0 = fmaxf(m0, x0), n1 = fmaxf(m1, x1);
                const float a0 = ex2((m0 - n0) * LOG2E), a1 = ex2((m1 - n1) * LOG2E);
                m0 = n0;
                m1 = n1;
                const float p0 = ex2((v[0] - n0) * LOG2E), p1 = ex2((v[1] - n1) * LOG2E);
                const float p2 = ex2((v[2] - n0) * LOG2E), p3 = ex2((v[3] - n1) * LOG2E);
                l0 = fmaf(l0, a0, p0 + p2);
                l1 = fmaf(l1, a1, p1 + p3);
                const uint32_t blo = movmat(pack_bf16(p0, p1));
                const uint32_t bhi = movmat(pack_bf16(p2, p3));
#pragma unroll
                for (int i = 0; i < 8; i++) {
                    o[i][0] *= a0;
                    o[i][1] *= a1;
                    o[i][2] *= a0;
                    o[i][3] *= a1;
                }
                const int vs_ = wait_item(ik + KG, 50);
                const uint32_t vaddr = voff + vs_ * SLOT;
#pragma unroll
                for (int i = 0; i < 4; i++) {
                    const uint32_t b0 = ((g >> 1) == i) ? blo : 0u, b1 = ((g >> 1) == i) ? bhi : 0u;
#pragma unroll
                    for (int md = 0; md < 8; md++) {
                        uint32_t a[4];
                        ldsm4t((vaddr ^ ((md & 3) << 5)) + (md >> 2) * (SLOT / 2) + i * 2048, a);
                        mma16816(o[md], a, b0, b1);
                    }
                }
                if (lane == 0) mbar_arrive4(empty0 + 8 * vs_);
            }
            float w0 = m0, w1 = m1;
#pragma unroll
            for (int off = 1; off <= 2; off <<= 1) {
                w0 = fmaxf(w0, __shfl_xor_sync(0xffffffffu, w0, off));
                w1 = fmaxf(w1, __shfl_xor_sync(0xffffffffu, w1, off));
            }
            const float s0 = ex2((m0 - w0) * LOG2E), s1 = ex2((m1 - w1) * LOG2E);
            l0 *= s0;
            l1 *= s1;
#pragma unroll
            for (int off = 1; off <= 16; off <<= 1) {
                l0 += __shfl_xor_sync(0xffffffffu, l0, off);
                l1 += __shfl_xor_sync(0xffffffffu, l1, off);
            }
            float* mo = reinterpret_cast<float*>(smem + OFF_MO);
            float* ml = reinterpret_cast<float*>(smem + OFF_ML);
#pragma unroll
            for (int md = 0; md < 8; md++) {
                float a = o[md][0] * s0, b = o[md][1] * s1, c = o[md][2] * s0, d = o[md][3] * s1;
                const bool u1 = t & 1, u2 = t & 2;
                float k0 = u2 ? c : a, k1 = u2 ? d : b, e0 = u2 ? a : c, e1 = u2 ? b : d;
                k0 += __shfl_xor_sync(0xffffffffu, e0, 2);
                k1 += __shfl_xor_sync(0xffffffffu, e1, 2);
                float k = u1 ? k1 : k0, e = u1 ? k0 : k1;
                k += __shfl_xor_sync(0xffffffffu, e, 1);
                mo[warp * 256 + (t & 1) * 128 + md * 16 + g + (t >> 1) * 8] = k;
            }
            if (lane == 0) {
                ml[warp * 4 + 0] = w0; ml[warp * 4 + 1] = l0; ml[warp * 4 + 2] = w1; ml[warp * 4 + 3] = l1;
            }
            named_bar(7, 32 * AW);
#pragma unroll 1
            for (int sl = warp; sl < 8; sl += AW) {
                const int hsel = sl >> 2;
                float M = -INFINITY;
#pragma unroll
                for (int w = 0; w < AW; w++) M = fmaxf(M, ml[w * 4 + hsel * 2]);
                float acc = 0.f, L = 0.f;
#pragma unroll
                for (int w = 0; w < AW; w++) {
                    const float sc = ex2((ml[w * 4 + hsel * 2] - M) * LOG2E);
                    acc = fmaf(mo[w * 256 + sl * 32 + lane], sc, acc);
                    L = fmaf(ml[w * 4 + hsel * 2 + 1], sc, L);
                }
                if (sl != (cta & 7)) {
                    st_pkt(&g_po[cta][sl][lane], pack_pkt(acc, tag));
                    if (lane < 8) st_pkt2(&g_po[cta][sl][32 + 2 * lane], pack_pkt(M, tag), pack_pkt(L, tag));
                } else {
                    float* own = reinterpret_cast<float*>(smem + OFF_OWN);
                    own[lane] = acc;
                    if (lane == 0) { own[32] = M; own[33] = L; }
                    named_arrive(5, 64);
                }
            }
        }
        if (warp == 4) {
            const float gv = bf16r(red_s[128 + lane] + red_s[160 + lane] + red_s[192 + lane] + red_s[224 + lane]);
            const float uv = bf16r(red_s[256 + lane] + red_s[288 + lane] + red_s[320 + lane] + red_s[352 + lane]);
            const float sg = bf16r(gv / (1.f + __expf(-gv)));
            reinterpret_cast<__nv_bfloat16*>(smem + OFF_H)[lane] = __float2bfloat16_rn(sg * uv);
        }
        const uint32_t roff = ((lr * 9 + warp) << 7) + (((mi & 1) ^ ((lr + warp) & 7)) << 4);
#pragma unroll 1
        for (int k = 0; k < (att ? 4 : 2); k++) {
            if (k == 0) named_bar(2, 288);
            if (k == 2) named_bar(1, 320);
            const uint32_t* v32 = reinterpret_cast<const uint32_t*>(smem + OFF_H) + 8 * k;
            const uint32_t b0 = v32[t], b1 = v32[4 + t];
            const int item = (att ? item_of_w(6) : XRING * u + 6) + 2 * k;
            const int q0 = att ? item / NSLOT : u, q1 = att ? (item + 1) / NSLOT : u;
            const int s0 = item - q0 * ring, s1 = item + 1 - q1 * ring;
            const uint32_t base = sbase + ((mi >> 1) ? s1 : s0) * SLOT;
            for (int it = 0; *issued_s <= item + 1 && it < SPIN_LIMIT; it++) __nanosleep(20);
            mbar_spin(full0 + 8 * s0, q0 & 1);
            mbar_spin(full0 + 8 * s1, q1 & 1);
            __syncwarp();
#pragma unroll
            for (int mt = 0; mt < 4; mt++) {
                uint32_t a[4];
                ldsm4t(base + (roff ^ (mt << 5)), a);
                mma16816(res[mt], a, b0, b1);
            }
        }
        if (!att) {
            named_bar(2, 288);
            if (tid < 4) mbar_arrive4(empty0 + 8 * (6 + tid));
            if (++u < 4) continue;
        }
        break;
    }
    {
        const float r0 = (t & 2) ? ((t & 1) ? res[3][0] : res[2][0]) : ((t & 1) ? res[1][0] : res[0][0]);
        const float r1 = (t & 2) ? ((t & 1) ? res[3][2] : res[2][2]) : ((t & 1) ? res[1][2] : res[0][2]);
        asm volatile("red.relaxed.gpu.global.add.v4.f32 [%0], {%1, %2, %3, %4};"
                     ::"l"(accp), "f"(r0), "f"(r1), "f"(1.0f), "f"(0.0f) : "memory");
    }

    if (!att) {
        const int slot = (cta - ATT_CTAS) * 72 + (tid >> 2), copy = tid & 3;
        const int col = (slot >> 3) * 16 + (slot & 7) + (copy & 1) * 8;
        float4* src = &g_acc[copy][slot];
        const float xv = __bfloat162float(x[col]);
        __nv_bfloat16* dst = out + col;
        asm volatile("" : "+l"(dst));
        unsigned long long a = 0, b = 0;
        if (warp == 0) {
#pragma unroll 1
            for (int it = 0; it < SPIN_LIMIT; it++) {
                float cnt = 0.f;
                if (lane < 4) {
                    ld_pkt2(reinterpret_cast<const unsigned long long*>(src), a, b);
                    cnt = pkt_val(b);
                }
                cnt += __shfl_xor_sync(0xffffffffu, cnt, 1);
                cnt += __shfl_xor_sync(0xffffffffu, cnt, 2);
                cnt = __shfl_sync(0xffffffffu, cnt, 0);
                if (cnt >= (float)(NCTA - FIN_X)) break;
                __nanosleep(cnt > 8.f ? 100 : 300);
            }
        }
        named_bar(2, 288);
#pragma unroll 1
        for (int it = 0; it < SPIN_LIMIT; it++) {
            ld_pkt2(reinterpret_cast<const unsigned long long*>(src), a, b);
            if (pkt_val(b) == (float)(NCTA / NCOPY)) break;
        }
        __syncwarp();
        const float s0 = pkt_val(a), s1 = __uint_as_float(pkt_tag(a));
        float k = (copy & 1) ? s1 : s0;
        k += __shfl_xor_sync(0xffffffffu, (copy & 1) ? s0 : s1, 1);
        k += __shfl_xor_sync(0xffffffffu, k, 2);
        if (copy < 2) *dst = __float2bfloat16_rn(xv + k);
        *src = make_float4(0.f, 0.f, 0.f, 0.f);
        if (cta == ATT_CTAS && tid == 0) g_epoch = tag;
    }
}

typedef CUresult (*EncodeFn)(CUtensorMap*, CUtensorMapDataType, cuuint32_t, void*, const cuuint64_t*, const cuuint64_t*,
                             const cuuint32_t*, const cuuint32_t*, CUtensorMapInterleave, CUtensorMapSwizzle,
                             CUtensorMapL2promotion, CUtensorMapFloatOOBfill);

void make_map(EncodeFn enc, CUtensorMap* m, void* base, uint64_t cols, uint64_t rows, uint32_t bc, uint32_t br,
              CUtensorMapSwizzle sw) {
    cuuint64_t gd[2] = {cols, rows};
    cuuint64_t gs[1] = {cols * 2};
    cuuint32_t bx[2] = {bc, br};
    cuuint32_t es[2] = {1, 1};
    enc(m, CU_TENSOR_MAP_DATA_TYPE_BFLOAT16, 2, base, gd, gs, bx, es, CU_TENSOR_MAP_INTERLEAVE_NONE, sw,
        CU_TENSOR_MAP_L2_PROMOTION_L2_256B, CU_TENSOR_MAP_FLOAT_OOB_FILL_NONE);
}

}

extern "C" void kernel_launch(void* const* d_in, const int* in_sizes, int n_in, void* d_out, int out_size) {
    (void)in_sizes; (void)n_in; (void)out_size;
    static EncodeFn enc = nullptr;
    static unsigned tau = 666;
    if (!enc) {
        int dev = 0, khz = 0, bits = 0;
        cudaGetDevice(&dev);
        if (cudaDeviceGetAttribute(&khz, cudaDevAttrMemoryClockRate, dev) == cudaSuccess &&
            cudaDeviceGetAttribute(&bits, cudaDevAttrGlobalMemoryBusWidth, dev) == cudaSuccess && khz > 0 && bits > 0)
            tau = (unsigned)(ATT_CTAS * 16384.0 / (BW_EFF * 2.0 * khz * 1e-6 * (bits / 8)) + 0.5);
        void* fn = nullptr;
        cudaDriverEntryPointQueryResult qr;
        cudaGetDriverEntryPoint("cuTensorMapEncodeTiled", &fn, cudaEnableDefault, &qr);
        enc = (EncodeFn)fn;
        cudaFuncSetAttribute(fused_decode_kernel, cudaFuncAttributeMaxDynamicSharedMemorySize, SMEM_BYTES);
    }
    Maps maps;
    make_map(enc, &maps.k, d_in[1], 128, 16 * 16384, 64, TP, CU_TENSOR_MAP_SWIZZLE_128B);
    make_map(enc, &maps.v, d_in[2], 128, 16 * 16384, 64, TP, CU_TENSOR_MAP_SWIZZLE_128B);
    make_map(enc, &maps.wq, d_in[3], NQ, D_MODEL, 32, 192, CU_TENSOR_MAP_SWIZZLE_64B);
    make_map(enc, &maps.wg, d_in[6], FF, D_MODEL, 32, 192, CU_TENSOR_MAP_SWIZZLE_64B);
    make_map(enc, &maps.wu, d_in[7], FF, D_MODEL, 32, 192, CU_TENSOR_MAP_SWIZZLE_64B);
    make_map(enc, &maps.wd, d_in[8], 64, FF * 9, 64, 72, CU_TENSOR_MAP_SWIZZLE_128B);
    make_map(enc, &maps.wo, d_in[4], 64, NQ * 9, 64, 72, CU_TENSOR_MAP_SWIZZLE_128B);
    fused_decode_kernel<<<NCTA, NTHREADS, SMEM_BYTES>>>(maps, (const __nv_bfloat16*)d_in[0], (__nv_bfloat16*)d_out, tau);
}
```

```cpp
#include <cuda_runtime.h>
#include <cuda.h>
#include <cuda_bf16.h>
#include <stdint.h>

namespace {

constexpr int D_MODEL = 576;
constexpr int NQ = 4096;
constexpr int FF = 4608;

constexpr int NCTA = 132;
constexpr int ATT_CTAS = 128;
constexpr int NTHREADS = 352;

constexpr int AW = 4;
constexpr int TP = 64;
constexpr int NT = 2048 / TP;
constexpr int SLOT = TP * 256;
constexpr int NSLOT = 13;
constexpr int CPB = 192 * 64;
constexpr int RPB = 8 * 1152;

#define DEPTH 8
#define TDEPTH 5
#define BW_EFF 0.947
#define T_OFF 500
#define XSLOW 10
#define POLL_AT 11
#define POLL_NS 200
#define GLAG 16
#define QPOLL_AT 6
#define FIN_X 110
constexpr int KG = 4;

constexpr int IT_KV = 3, IT_W = IT_KV + 2 * NT, IT_END = IT_W + 14, XRING = 10;
static_assert(KG == AW && NT == 8 * KG, "one group of tiles per kv head");
__device__ constexpr int item_of_w(int j) { return IT_W + j; }

constexpr int OFF_RED = NSLOT * SLOT;
constexpr int OFF_XN = OFF_RED + 3 * 4 * 32 * 4;
constexpr int OFF_Q = OFF_XN + D_MODEL * 2;
constexpr int OFF_H = OFF_Q + 4096;
constexpr int OFF_O = OFF_H + 64;
constexpr int OFF_MO = OFF_O + 64;
constexpr int OFF_ML = OFF_MO + 2 * AW * 256 * 4;
constexpr int OFF_BAR = OFF_ML + 2 * AW * 16;
constexpr int OFF_ISSUED = OFF_BAR + (2 * NSLOT + 8) * 8;
constexpr int SMEM_BYTES = OFF_ISSUED + 16 + 1024;
static_assert(SMEM_BYTES <= 232448, "smem");

constexpr int NCOPY = 4;
constexpr int SPIN_LIMIT = 1 << 17;
constexpr int WAIT_LIMIT = 1 << 17;
constexpr float LOG2E = 1.4426950408889634f;

__device__ unsigned g_epoch;
__device__ __align__(128) unsigned long long g_q[NQ / 2];
__device__ __align__(128) uint32_t g_po[16][8][64][32];
__device__ __align__(128) uint32_t g_ml[16][64][32];
__device__ __align__(128) float4 g_acc[NCOPY][288];

__device__ __forceinline__ uint32_t smem_u32(const void* p) { return (uint32_t)__cvta_generic_to_shared(p); }
__device__ __forceinline__ void mbar_init(uint32_t bar, uint32_t cnt) {
    asm volatile("mbarrier.init.shared::cta.b64 [%0], %1;" ::"r"(bar), "r"(cnt) : "memory");
}
__device__ __forceinline__ void mbar_expect_tx(uint32_t bar, uint32_t bytes) {
    asm volatile("mbarrier.arrive.expect_tx.shared::cta.b64 _, [%0], %1;" ::"r"(bar), "r"(bytes) : "memory");
}
__device__ __forceinline__ void mbar_arrive(uint32_t bar) {
    asm volatile("mbarrier.arrive.shared::cta.b64 _, [%0];" ::"r"(bar) : "memory");
}
__device__ __forceinline__ void mbar_arrive4(uint32_t bar) {
    asm volatile("mbarrier.arrive.shared::cta.b64 _, [%0], 4;" ::"r"(bar) : "memory");
}
__device__ __forceinline__ void mbar_wait(uint32_t bar, uint32_t parity) {
    for (int it = 0; it < WAIT_LIMIT; it++) {
        uint32_t ok;
        asm volatile(
            "{\n.reg .pred p;\n"
            "mbarrier.try_wait.parity.shared::cta.b64 p, [%1], %2, %3;\n"
            "selp.u32 %0, 1, 0, p;\n}\n"
            : "=r"(ok) : "r"(bar), "r"(parity), "r"(1000) : "memory");
        if (ok) break;
    }
}
__device__ __forceinline__ void mbar_spin(uint32_t bar, uint32_t parity) {
    for (int it = 0; it < (1 << 22); it++) {
        uint32_t ok;
        asm volatile(
            "{\n.reg .pred p;\n"
            "mbarrier.test_wait.parity.shared::cta.b64 p, [%1], %2;\n"
            "selp.u32 %0, 1, 0, p;\n}\n"
            : "=r"(ok) : "r"(bar), "r"(parity) : "memory");
        if (ok) break;
    }
}
__device__ __forceinline__ unsigned long long gtime() {
    unsigned long long t;
    asm volatile("mov.u64 %0, %globaltimer;" : "=l"(t));
    return t;
}
__device__ __forceinline__ void tma2d(uint32_t dst, const CUtensorMap* map, int c0, int c1, uint32_t bar, uint64_t pol) {
    asm volatile(
        "cp.async.bulk.tensor.2d.shared::cluster.global.mbarrier::complete_tx::bytes.L2::cache_hint "
        "[%0], [%1, {%3, %4}], [%2], %5;"
        ::"r"(dst), "l"(map), "r"(bar), "r"(c0), "r"(c1), "l"(pol) : "memory");
}
__device__ __forceinline__ unsigned long long pack_pkt(float v, unsigned tag) {
    return (unsigned long long)__float_as_uint(v) | ((unsigned long long)tag << 32);
}
__device__ __forceinline__ void st_pkt(unsigned long long* p, unsigned long long v) {
    asm volatile("st.relaxed.gpu.global.b64 [%0], %1;" ::"l"(p), "l"(v) : "memory");
}
__device__ __forceinline__ void ld_pkt2(const unsigned long long* p, unsigned long long& a, unsigned long long& b) {
    asm volatile("ld.relaxed.gpu.global.v2.b64 {%0, %1}, [%2];" : "=l"(a), "=l"(b) : "l"(p) : "memory");
}
__device__ __forceinline__ void st_word(uint32_t* p, float v, unsigned tag) {
    asm volatile("st.relaxed.gpu.global.u32 [%0], %1;" ::"l"(p), "r"((__float_as_uint(v) & ~15u) | (tag & 15u)) : "memory");
}
__device__ __forceinline__ uint4 ld_word4(const uint32_t* p) {
    uint4 v;
    asm volatile("ld.relaxed.gpu.global.v4.u32 {%0,%1,%2,%3}, [%4];" : "=r"(v.x), "=r"(v.y), "=r"(v.z), "=r"(v.w) : "l"(p) : "memory");
    return v;
}
__device__ __forceinline__ bool fresh4(const uint4& v, unsigned tag) {
    return (((v.x ^ tag) | (v.y ^ tag) | (v.z ^ tag) | (v.w ^ tag)) & 15u) == 0;
}
__device__ __forceinline__ float word_val(uint32_t v) { return __uint_as_float(v & ~15u); }
__device__ __forceinline__ float pkt_val(unsigned long long v) { return __uint_as_float((unsigned)v); }
__device__ __forceinline__ unsigned pkt_tag(unsigned long long v) { return (unsigned)(v >> 32); }

__device__ __forceinline__ float bf16r(float v) { return __bfloat162float(__float2bfloat16_rn(v)); }
__device__ __forceinline__ float bf_lo(uint32_t v) { return __uint_as_float(v << 16); }
__device__ __forceinline__ float bf_hi(uint32_t v) { return __uint_as_float(v & 0xffff0000u); }
__device__ __forceinline__ uint32_t pack_bf16(float lo, float hi) {
    uint32_t r;
    asm("cvt.rn.bf16x2.f32 %0, %1, %2;" : "=r"(r) : "f"(hi), "f"(lo));
    return r;
}
__device__ __forceinline__ float ex2(float x) {
    float r;
    asm("ex2.approx.ftz.f32 %0, %1;" : "=f"(r) : "f"(x));
    return r;
}
__device__ __forceinline__ void ldsm4(uint32_t addr, uint32_t (&r)[4]) {
    asm volatile("ldmatrix.sync.aligned.m8n8.x4.shared.b16 {%0,%1,%2,%3}, [%4];"
                 : "=r"(r[0]), "=r"(r[1]), "=r"(r[2]), "=r"(r[3]) : "r"(addr) : "memory");
}
__device__ __forceinline__ void ldsm4t(uint32_t addr, uint32_t (&r)[4]) {
    asm volatile("ldmatrix.sync.aligned.m8n8.x4.trans.shared.b16 {%0,%1,%2,%3}, [%4];"
                 : "=r"(r[0]), "=r"(r[1]), "=r"(r[2]), "=r"(r[3]) : "r"(addr) : "memory");
}
__device__ __forceinline__ void mma16816(float (&c)[4], const uint32_t (&a)[4], uint32_t b0, uint32_t b1) {
    asm volatile(
        "mma.sync.aligned.m16n8k16.row.col.f32.bf16.bf16.f32 {%0,%1,%2,%3}, {%4,%5,%6,%7}, {%8,%9}, {%0,%1,%2,%3};"
        : "+f"(c[0]), "+f"(c[1]), "+f"(c[2]), "+f"(c[3])
        : "r"(a[0]), "r"(a[1]), "r"(a[2]), "r"(a[3]), "r"(b0), "r"(b1));
}
__device__ __forceinline__ uint32_t movmat(uint32_t a) {
    uint32_t d;
    asm volatile("movmatrix.sync.aligned.m8n8.trans.b16 %0, %1;" : "=r"(d) : "r"(a));
    return d;
}
__device__ __forceinline__ void named_bar(int id, int n) {
    asm volatile("bar.sync %0, %1;" ::"r"(id), "r"(n) : "memory");
}
__device__ __forceinline__ void named_arrive(int id, int n) {
    asm volatile("bar.arrive %0, %1;" ::"r"(id), "r"(n) : "memory");
}

struct Maps {
    CUtensorMap k, v, wq, wg, wu, wd, wo;
};

__global__ void __launch_bounds__(NTHREADS, 1)
fused_decode_kernel(const __grid_constant__ Maps maps, const __nv_bfloat16* __restrict__ x,
                    __nv_bfloat16* __restrict__ out, const unsigned tau) {
    extern __shared__ unsigned char smem_raw[];
    const uint32_t sbase = (smem_u32(smem_raw) + 1023u) & ~1023u;
    const uint32_t full0 = sbase + OFF_BAR, empty0 = full0 + 8 * NSLOT, qbar0 = empty0 + 8 * NSLOT;
    const int tid = threadIdx.x, cta = blockIdx.x;
    const bool att = cta < ATT_CTAS;
    unsigned char* smem = smem_raw + (sbase - smem_u32(smem_raw));
    volatile int* issued_s = reinterpret_cast<volatile int*>(smem + OFF_ISSUED);
    const int ring = att ? NSLOT : XRING;
    if (tid >= 288 && tid < 320) {
        if (tid != 288) asm volatile("exit;");
        const unsigned t0 = (unsigned)gtime();
        uint64_t pol, polw;
#pragma unroll
        for (int b = 0; b < 3; b++) mbar_init(full0 + 8 * b, 1);
        asm volatile("fence.mbarrier_init.release.cluster;" ::: "memory");
        asm volatile("createpolicy.fractional.L2::evict_normal.b64 %0, 1.0;" : "=l"(polw));
        int unit = att ? cta : ATT_CTAS + (cta - ATT_CTAS) * 4;
#pragma unroll
        for (int b = 0; b < 3; b++) {
            mbar_expect_tx(full0 + 8 * b, CPB);
            tma2d(sbase + b * SLOT, att ? &maps.wq : (b & 1) ? &maps.wu : &maps.wg, unit * 32, (att ? b : b >> 1) * 192,
                  full0 + 8 * b, polw);
        }
#pragma unroll 1
        for (int i = 0; i < 7; i++) asm volatile("prefetch.tensormap [%0];" ::"l"(&maps.k + i) : "memory");
#pragma unroll 1
        for (int i = 3; i < 2 * NSLOT + 8; i++) mbar_init(full0 + 8 * i, i >= NSLOT && i < 2 * NSLOT ? 4 : 1);
        *issued_s = 3;
        asm volatile("fence.mbarrier_init.release.cluster;" ::: "memory");
        named_arrive(6, NTHREADS);
        asm volatile("createpolicy.fractional.L2::evict_first.b64 %0, 1.0;" : "=l"(pol));
        const int nitems = att ? IT_END : 4 * XRING;
        int slot = 3, ph = 0, lslot = 0, lph = 0, landed = 0, depth = DEPTH;
        unsigned due = T_OFF << 4;
        int n = att ? 0 : NT, half = 0, j = att ? 0 : 3;
#pragma unroll 1
        for (int i = 3; i < nitems; i++) {
            if (!att && j == XRING) { j = 0; unit++; }
            const uint32_t bar = full0 + 8 * slot, dst = sbase + slot * SLOT;
            if (i >= ring) mbar_wait(empty0 + 8 * slot, ph ^ 1);
            while (landed <= i - depth) {
                mbar_wait(full0 + 8 * lslot, lph);
                landed++;
                if (++lslot == ring) { lslot = 0; lph ^= 1; }
            }
            if (n < NT || !att)
                for (int it = 0; (int)((unsigned)gtime() - t0 - (due >> 4)) < 0 && it < (1 << 22); it++) {}
            uint32_t bytes;
            if (n < NT) {
                const CUtensorMap* m = half >= KG ? &maps.v : &maps.k;
                const int row = (cta >> 6) * (8 * 16384) + ((n + (half >= KG ? half - KG : half)) * 64 + (cta & 63)) * TP;
                bytes = SLOT;
                mbar_expect_tx(bar, SLOT);
                tma2d(dst, m, 0, row, bar, pol);
                tma2d(dst + SLOT / 2, m, 64, row, bar, pol);
                if (++half == 2 * KG) { half = 0; n += KG; }
            } else if (j < 6) {
                const CUtensorMap* m = (j & 1) ? &maps.wu : &maps.wg;
                bytes = CPB;
                mbar_expect_tx(bar, CPB);
                tma2d(dst, m, unit * 32, (j >> 1) * 192, bar, polw);
                j++;
            } else {
                bytes = RPB;
                mbar_expect_tx(bar, RPB);
                tma2d(dst, j < 10 ? &maps.wd : &maps.wo, 0, unit * 288 + ((j - 6) & 3) * 72, bar, pol);
                j++;
            }
            due += (bytes >> 10) * (att ? tau : tau * XSLOW / 4);
            *issued_s = i + 1;
            if (n == NT) depth = TDEPTH;
            if (++slot == ring) { slot = 0; ph ^= 1; }
        }
        asm volatile("exit;");
    }
    const int lane = tid & 31;
    const int warp = __shfl_sync(0xffffffffu, tid >> 5, 0);
    float* red_s = reinterpret_cast<float*>(smem + OFF_RED);
    uint32_t* xn32 = reinterpret_cast<uint32_t*>(smem + OFF_XN);
    const int g = lane >> 2, t = lane & 3;
    const int lr = lane & 7, mi = lane >> 3;

    auto wait_item = [&](int i, int sleep_ns) {
        for (int it = 0; *issued_s <= i && it < SPIN_LIMIT; it++) __nanosleep(sleep_ns);
        const int q = att ? i / NSLOT : i / XRING, sl = i - q * ring;
        mbar_wait(full0 + 8 * sl, q & 1);
        __syncwarp();
        return sl;
    };

    unsigned tag = 0;
    asm volatile("ld.relaxed.gpu.global.u32 %0, [%1];" : "=r"(tag) : "l"(&g_epoch) : "memory");
    if (warp < 9) {
        uint32_t xs[9];
#pragma unroll
        for (int i = 0; i < 9; i++) xs[i] = __ldg(reinterpret_cast<const uint32_t*>(x) + lane + 32 * i);
        float s = 0.f;
#pragma unroll
        for (int i = 0; i < 9; i++) s += bf_lo(xs[i]) + bf_hi(xs[i]);
#pragma unroll
        for (int o = 16; o; o >>= 1) s += __shfl_xor_sync(0xffffffffu, s, o);
        const float mean = s * (1.f / D_MODEL);
        float vs = 0.f;
#pragma unroll
        for (int i = 0; i < 9; i++) {
            float a = bf_lo(xs[i]) - mean, b = bf_hi(xs[i]) - mean;
            vs += a * a + b * b;
        }
#pragma unroll
        for (int o = 16; o; o >>= 1) vs += __shfl_xor_sync(0xffffffffu, vs, o);
        const float mb = bf16r(mean);
        const float den = bf16r(sqrtf(bf16r(bf16r(vs * (1.f / D_MODEL)) + 1e-5f)));
        uint32_t mine = xs[0];
#pragma unroll
        for (int i = 1; i < 9; i++) mine = (warp == i) ? xs[i] : mine;
        xn32[tid] = pack_bf16(bf16r(bf_lo(mine) - mb) / den, bf16r(bf_hi(mine) - mb) / den);
    }
    named_bar(6, NTHREADS);
    tag += 1;

    if (warp == 10) {
        if (!att) return;
        const int H = cta >> 3, eo = H & 7;
        wait_item(QPOLL_AT, 100);
#pragma unroll 1
        for (int e = 0; e < 9; e++) {
            if (e < 8) {
                if (e > 1)
                    for (int it = 0; *issued_s < IT_KV + 2 * KG * (e - 1) && it < SPIN_LIMIT; it++) __nanosleep(200);
                const unsigned long long* src = &g_q[(cta >> 6) * 1024 + e * 128 + lane * 2];
                unsigned long long a[2], b[2];
                for (int it = 0; it < SPIN_LIMIT; it++) {
                    ld_pkt2(src, a[0], b[0]);
                    ld_pkt2(src + 64, a[1], b[1]);
                    if (pkt_tag(a[0]) == tag && pkt_tag(b[0]) == tag && pkt_tag(a[1]) == tag && pkt_tag(b[1]) == tag) break;
                    __nanosleep(200);
                }
                uint2* qs = reinterpret_cast<uint2*>(smem + OFF_Q) + e * 64 + lane;
                qs[0] = make_uint2((unsigned)a[0], (unsigned)b[0]);
                qs[32] = make_uint2((unsigned)a[1], (unsigned)b[1]);
                __syncwarp();
                if (lane == 0) mbar_arrive(qbar0 + 8 * e);
            }
            if (e != min(eo + 4, 8)) continue;
            const int when = min(IT_KV + 2 * KG * (eo + 1) + GLAG, IT_W + POLL_AT);
            for (int it = 0; *issued_s < when && it < SPIN_LIMIT; it++) __nanosleep(100);
            const uint32_t* src = &g_po[H][cta & 7][0][lane * 4];
            uint4 a[18];
            unsigned pend = 0x3ffffu;
            for (int it = 0; pend && it < SPIN_LIMIT; it++) {
                if (it) __nanosleep(POLL_NS);
#pragma unroll
                for (int j = 0; j < 18; j++)
                    if (pend >> j & 1) a[j] = ld_word4(j < 16 ? src + j * 128 : &g_ml[H][lane + (j - 16) * 32][0]);
#pragma unroll
                for (int j = 0; j < 18; j++)
                    if (fresh4(a[j], tag)) pend &= ~(1u << j);
            }
            __syncwarp();
            const bool hs = cta & 4;
            const float m0 = word_val(hs ? a[16].z : a[16].x), m1 = word_val(hs ? a[17].z : a[17].x);
            float M = fmaxf(m0, m1);
#pragma unroll
            for (int off = 16; off; off >>= 1) M = fmaxf(M, __shfl_xor_sync(0xffffffffu, M, off));
            const float w0 = ex2((m0 - M) * LOG2E), w1 = ex2((m1 - M) * LOG2E);
            float L = w0 * word_val(hs ? a[16].w : a[16].y) + w1 * word_val(hs ? a[17].w : a[17].y);
#pragma unroll
            for (int off = 16; off; off >>= 1) L += __shfl_xor_sync(0xffffffffu, L, off);
            float acc[4] = {};
#pragma unroll
            for (int j = 0; j < 16; j++) {
                const float w = __shfl_sync(0xffffffffu, j < 8 ? w0 : w1, (4 * j + (lane >> 3)) & 31);
                acc[0] = fmaf(word_val(a[j].x), w, acc[0]);
                acc[1] = fmaf(word_val(a[j].y), w, acc[1]);
                acc[2] = fmaf(word_val(a[j].z), w, acc[2]);
                acc[3] = fmaf(word_val(a[j].w), w, acc[3]);
            }
#pragma unroll
            for (int i = 0; i < 4; i++) {
                acc[i] += __shfl_xor_sync(0xffffffffu, acc[i], 8);
                acc[i] += __shfl_xor_sync(0xffffffffu, acc[i], 16);
            }
            if (lane < 8)
                reinterpret_cast<uint2*>(smem + OFF_O)[lane] =
                    make_uint2(pack_bf16(acc[0] / L, acc[1] / L), pack_bf16(acc[2] / L, acc[3] / L));
        }
        __syncwarp();
        named_arrive(1, 320);
        return;
    }

    float res[4][4] = {};
    float4* accp = &g_acc[cta % NCOPY][warp * 32 + t * 8 + g];
    asm volatile("" : "+l"(accp));
#pragma unroll 1
    for (int u = 0;;) {
        if (warp >= 4 && warp < 8) {
            const int fw = warp - 4;
            const uint32_t coff = ((fw * 48 + (mi >> 1) * 8 + lr) << 6) + (((mi & 1) ^ ((lr >> 1) & 3)) << 4);
            float s0 = 0.f, s1 = 0.f;
#pragma unroll 1
            for (int p = att ? -3 : 0; p < 6; p++) {
                const int pc = p < 0 ? p + 3 : p >> 1;
                uint32_t b[3][2];
#pragma unroll
                for (int ks = 0; ks < 3; ks++) {
                    b[ks][0] = xn32[pc * 96 + fw * 24 + ks * 8 + t];
                    b[ks][1] = xn32[pc * 96 + fw * 24 + ks * 8 + 4 + t];
                }
                const int sl = wait_item(p < 0 ? pc : att ? item_of_w(p) : XRING * u + p, 200);
                float acc[2][4] = {};
#pragma unroll
                for (int ks = 0; ks < 3; ks++)
#pragma unroll
                    for (int mt = 0; mt < 2; mt++) {
                        uint32_t a[4];
                        ldsm4t(sbase + sl * SLOT + ((coff + ks * 1024) ^ (mt << 5)), a);
                        mma16816(acc[mt], a, b[ks][0], b[ks][1]);
                    }
                if (lane == 0) mbar_arrive(empty0 + 8 * sl);
                const float val = (t & 2) ? ((t & 1) ? acc[1][2] : acc[1][0]) : ((t & 1) ? acc[0][2] : acc[0][0]);
                if (p >= 0 && (p & 1)) s1 += val; else s0 += val;
                if (p == -1 || p == 5) {
                    const int o = p < 0 ? 0 : 128;
                    red_s[o + fw * 32 + 8 * t + g] = s0;
                    red_s[256 + fw * 32 + 8 * t + g] = s1;
                    s0 = 0.f;
                    named_bar(3, 128);
                    if (p < 0 && warp == 4) {
                        const float qv = red_s[lane] + red_s[32 + lane] + red_s[64 + lane] + red_s[96 + lane];
                        const uint32_t q2 = pack_bf16(qv, __shfl_down_sync(0xffffffffu, qv, 1));
                        if (!(lane & 1)) st_pkt(&g_q[cta * 16 + (lane >> 1)], pack_pkt(__uint_as_float(q2), tag));
                    }
                }
            }
        } else if (att && warp < AW) {
            const uint32_t koff = sbase + ((mi & 1) * 8 + lr) * 128 + (((mi >> 1) ^ lr) << 4);
            const uint32_t voff = sbase + ((mi >> 1) * 8 + lr) * 128 + (((mi & 1) ^ lr) << 4);
            constexpr float SCALE = 0.08838834764831845f;
#pragma unroll 1
            for (int e = 0; e < 8; e++) {
                mbar_wait(qbar0 + 8 * e, 0);
                uint32_t qf[8][2];
                const uint32_t* q32 = reinterpret_cast<const uint32_t*>(smem + OFF_Q) + e * 128 + (g & 1) * 64 + t;
#pragma unroll
                for (int ks = 0; ks < 8; ks++) {
                    qf[ks][0] = q32[ks * 8];
                    qf[ks][1] = q32[ks * 8 + 4];
                }
                const int ik = IT_KV + 2 * KG * e + warp;
                const int ks_ = wait_item(ik, 50);
                const uint32_t kaddr = koff + ks_ * SLOT;
                float sc[4][4] = {};
#pragma unroll
                for (int ks = 0; ks < 8; ks++) {
#pragma unroll
                    for (int i = 0; i < 4; i++) {
                        uint32_t a[4];
                        ldsm4((kaddr ^ ((ks & 3) << 5)) + (ks >> 2) * (SLOT / 2) + i * 2048, a);
                        mma16816(sc[i], a, qf[ks][0], qf[ks][1]);
                    }
                }
                if (lane == 0) mbar_arrive4(empty0 + 8 * ks_);
                float v[4];
#pragma unroll
                for (int j = 0; j < 4; j++) {
                    float a = (t & 1) ? sc[1][j] : sc[0][j];
                    float b = (t & 1) ? sc[3][j] : sc[2][j];
                    v[j] = bf16r(bf16r((t & 2) ? b : a) * SCALE);
                }
                float m0 = fmaxf(v[0], v[2]), m1 = fmaxf(v[1], v[3]);
#pragma unroll
                for (int off = 1; off <= 16; off <<= 1) {
                    m0 = fmaxf(m0, __shfl_xor_sync(0xffffffffu, m0, off));
                    m1 = fmaxf(m1, __shfl_xor_sync(0xffffffffu, m1, off));
                }
                const float p0 = ex2((v[0] - m0) * LOG2E), p1 = ex2((v[1] - m1) * LOG2E);
                const float p2 = ex2((v[2] - m0) * LOG2E), p3 = ex2((v[3] - m1) * LOG2E);
                const uint32_t blo = movmat(pack_bf16(p0, p1));
                const uint32_t bhi = movmat(pack_bf16(p2, p3));
                float l0 = p0 + p2, l1 = p1 + p3;
#pragma unroll
                for (int off = 1; off <= 16; off <<= 1) {
                    l0 += __shfl_xor_sync(0xffffffffu, l0, off);
                    l1 += __shfl_xor_sync(0xffffffffu, l1, off);
                }
                float* mo = reinterpret_cast<float*>(smem + OFF_MO) + (e & 1) * (AW * 256);
                float* ml = reinterpret_cast<float*>(smem + OFF_ML) + (e & 1) * (AW * 4);
                if (lane == 0) *reinterpret_cast<float4*>(ml + warp * 4) = make_float4(m0, l0, m1, l1);
                const int vs_ = wait_item(ik + KG, 50);
                const uint32_t vaddr = voff + vs_ * SLOT;
                float o[8][4] = {};
#pragma unroll
                for (int i = 0; i < 4; i++) {
                    const uint32_t b0 = ((g >> 1) == i) ? blo : 0u, b1 = ((g >> 1) == i) ? bhi : 0u;
#pragma unroll
                    for (int md = 0; md < 8; md++) {
                        uint32_t a[4];
                        ldsm4t((vaddr ^ ((md & 3) << 5)) + (md >> 2) * (SLOT / 2) + i * 2048, a);
                        mma16816(o[md], a, b0, b1);
                    }
                }
                if (lane == 0) mbar_arrive4(empty0 + 8 * vs_);
#pragma unroll
                for (int md = 0; md < 8; md++) {
                    const bool u1 = t & 1, u2 = t & 2;
                    float k0 = u2 ? o[md][2] : o[md][0], k1 = u2 ? o[md][3] : o[md][1];
                    k0 += __shfl_xor_sync(0xffffffffu, u2 ? o[md][0] : o[md][2], 2);
                    k1 += __shfl_xor_sync(0xffffffffu, u2 ? o[md][1] : o[md][3], 2);
                    float k = u1 ? k1 : k0;
                    k += __shfl_xor_sync(0xffffffffu, u1 ? k0 : k1, 1);
                    mo[warp * 256 + (t & 1) * 128 + md * 16 + g + (t >> 1) * 8] = k;
                }
                named_bar(7, 32 * AW);
                const int H = (cta >> 6) * 8 + e;
                float Mh[2], Lh[2];
#pragma unroll
                for (int hs = 0; hs < 2; hs++) {
                    float M = -INFINITY, acc = 0.f, L = 0.f;
#pragma unroll
                    for (int w = 0; w < AW; w++) M = fmaxf(M, ml[w * 4 + hs * 2]);
#pragma unroll
                    for (int w = 0; w < AW; w++) {
                        const float f = ex2((ml[w * 4 + hs * 2] - M) * LOG2E);
                        acc = fmaf(mo[w * 256 + hs * 128 + warp * 32 + lane], f, acc);
                        L = fmaf(ml[w * 4 + hs * 2 + 1], f, L);
                    }
                    st_word(&g_po[H][hs * 4 + warp][cta & 63][lane], acc, tag);
                    Mh[hs] = M;
                    Lh[hs] = L;
                }
                if (warp == 0)
                    st_word(&g_ml[H][cta & 63][lane], (lane & 2) ? ((lane & 1) ? Lh[1] : Mh[1]) : ((lane & 1) ? Lh[0] : Mh[0]), tag);
            }
        }
        if (warp == 4) {
            const float gv = bf16r(red_s[128 + lane] + red_s[160 + lane] + red_s[192 + lane] + red_s[224 + lane]);
            const float uv = bf16r(red_s[256 + lane] + red_s[288 + lane] + red_s[320 + lane] + red_s[352 + lane]);
            const float sg = bf16r(gv / (1.f + __expf(-gv)));
            reinterpret_cast<__nv_bfloat16*>(smem + OFF_H)[lane] = __float2bfloat16_rn(sg * uv);
        }
        const uint32_t roff = ((lr * 9 + warp) << 7) + (((mi & 1) ^ ((lr + warp) & 7)) << 4);
#pragma unroll 1
        for (int k = 0; k < (att ? 4 : 2); k++) {
            if (k == 0) named_bar(2, 288);
            if (k == 2) named_bar(1, 320);
            const uint32_t* v32 = reinterpret_cast<const uint32_t*>(smem + OFF_H) + 8 * k;
            const uint32_t b0 = v32[t], b1 = v32[4 + t];
            const int item = (att ? item_of_w(6) : XRING * u + 6) + 2 * k;
            const int q0 = att ? item / NSLOT : u, q1 = att ? (item + 1) / NSLOT : u;
            const int s0 = item - q0 * ring, s1 = item + 1 - q1 * ring;
            const uint32_t base = sbase + ((mi >> 1) ? s1 : s0) * SLOT;
            for (int it = 0; *issued_s <= item + 1 && it < SPIN_LIMIT; it++) __nanosleep(20);
            mbar_spin(full0 + 8 * s0, q0 & 1);
            mbar_spin(full0 + 8 * s1, q1 & 1);
            __syncwarp();
#pragma unroll
            for (int mt = 0; mt < 4; mt++) {
                uint32_t a[4];
                ldsm4t(base + (roff ^ (mt << 5)), a);
                mma16816(res[mt], a, b0, b1);
            }
        }
        if (!att) {
            named_bar(2, 288);
            if (tid < 4) mbar_arrive4(empty0 + 8 * (6 + tid));
            if (++u < 4) continue;
        }
        break;
    }
    {
        const float r0 = (t & 2) ? ((t & 1) ? res[3][0] : res[2][0]) : ((t & 1) ? res[1][0] : res[0][0]);
        const float r1 = (t & 2) ? ((t & 1) ? res[3][2] : res[2][2]) : ((t & 1) ? res[1][2] : res[0][2]);
        asm volatile("red.relaxed.gpu.global.add.v4.f32 [%0], {%1, %2, %3, %4};"
                     ::"l"(accp), "f"(r0), "f"(r1), "f"(1.0f), "f"(0.0f) : "memory");
    }

    if (!att) {
        const int slot = (cta - ATT_CTAS) * 72 + (tid >> 2), copy = tid & 3;
        const int col = (slot >> 3) * 16 + (slot & 7) + (copy & 1) * 8;
        float4* src = &g_acc[copy][slot];
        const float xv = __bfloat162float(x[col]);
        __nv_bfloat16* dst = out + col;
        asm volatile("" : "+l"(dst));
        unsigned long long a = 0, b = 0;
        if (warp == 0) {
#pragma unroll 1
            for (int it = 0; it < SPIN_LIMIT; it++) {
                float cnt = 0.f;
                if (lane < 4) {
                    ld_pkt2(reinterpret_cast<const unsigned long long*>(src), a, b);
                    cnt = pkt_val(b);
                }
                cnt += __shfl_xor_sync(0xffffffffu, cnt, 1);
                cnt += __shfl_xor_sync(0xffffffffu, cnt, 2);
                cnt = __shfl_sync(0xffffffffu, cnt, 0);
                if (cnt >= (float)(NCTA - FIN_X)) break;
                __nanosleep(cnt > 8.f ? 100 : 300);
            }
        }
        named_bar(2, 288);
#pragma unroll 1
        for (int it = 0; it < SPIN_LIMIT; it++) {
            ld_pkt2(reinterpret_cast<const unsigned long long*>(src), a, b);
            if (pkt_val(b) == (float)(NCTA / NCOPY)) break;
        }
        __syncwarp();
        const float s0 = pkt_val(a), s1 = __uint_as_float(pkt_tag(a));
        float k = (copy & 1) ? s1 : s0;
        k += __shfl_xor_sync(0xffffffffu, (copy & 1) ? s0 : s1, 1);
        k += __shfl_xor_sync(0xffffffffu, k, 2);
        if (copy < 2) *dst = __float2bfloat16_rn(xv + k);
        *src = make_float4(0.f, 0.f, 0.f, 0.f);
        if (cta == ATT_CTAS && tid == 0) g_epoch = tag;
    }
}

typedef CUresult (*EncodeFn)(CUtensorMap*, CUtensorMapDataType, cuuint32_t, void*, const cuuint64_t*, const cuuint64_t*,
                             const cuuint32_t*, const cuuint32_t*, CUtensorMapInterleave, CUtensorMapSwizzle,
                             CUtensorMapL2promotion, CUtensorMapFloatOOBfill);

void make_map(EncodeFn enc, CUtensorMap* m, void* base, uint64_t cols, uint64_t rows, uint32_t bc, uint32_t br,
              CUtensorMapSwizzle sw) {
    cuuint64_t gd[2] = {cols, rows};
    cuuint64_t gs[1] = {cols * 2};
    cuuint32_t bx[2] = {bc, br};
    cuuint32_t es[2] = {1, 1};
    enc(m, CU_TENSOR_MAP_DATA_TYPE_BFLOAT16, 2, base, gd, gs, bx, es, CU_TENSOR_MAP_INTERLEAVE_NONE, sw,
        CU_TENSOR_MAP_L2_PROMOTION_L2_256B, CU_TENSOR_MAP_FLOAT_OOB_FILL_NONE);
}

}

extern "C" void kernel_launch(void* const* d_in, const int* in_sizes, int n_in, void* d_out, int out_size) {
    (void)in_sizes; (void)n_in; (void)out_size;
    static EncodeFn enc = nullptr;
    static unsigned tau = 661;
    if (!enc) {
        int dev = 0, khz = 0, bits = 0;
        cudaGetDevice(&dev);
        if (cudaDeviceGetAttribute(&khz, cudaDevAttrMemoryClockRate, dev) == cudaSuccess &&
            cudaDeviceGetAttribute(&bits, cudaDevAttrGlobalMemoryBusWidth, dev) == cudaSuccess && khz > 0 && bits > 0)
            tau = (unsigned)(ATT_CTAS * 16384.0 / (BW_EFF * 2.0 * khz * 1e-6 * (bits / 8)) + 0.5);
        void* fn = nullptr;
        cudaDriverEntryPointQueryResult qr;
        cudaGetDriverEntryPoint("cuTensorMapEncodeTiled", &fn, cudaEnableDefault, &qr);
        enc = (EncodeFn)fn;
        cudaFuncSetAttribute(fused_decode_kernel, cudaFuncAttributeMaxDynamicSharedMemorySize, SMEM_BYTES);
    }
    Maps maps;
    make_map(enc, &maps.k, d_in[1], 128, 16 * 16384, 64, TP, CU_TENSOR_MAP_SWIZZLE_128B);
    make_map(enc, &maps.v, d_in[2], 128, 16 * 16384, 64, TP, CU_TENSOR_MAP_SWIZZLE_128B);
    make_map(enc, &maps.wq, d_in[3], NQ, D_MODEL, 32, 192, CU_TENSOR_MAP_SWIZZLE_64B);
    make_map(enc, &maps.wg, d_in[6], FF, D_MODEL, 32, 192, CU_TENSOR_MAP_SWIZZLE_64B);
    make_map(enc, &maps.wu, d_in[7], FF, D_MODEL, 32, 192, CU_TENSOR_MAP_SWIZZLE_64B);
    make_map(enc, &maps.wd, d_in[8], 64, FF * 9, 64, 72, CU_TENSOR_MAP_SWIZZLE_128B);
    make_map(enc, &maps.wo, d_in[4], 64, NQ * 9, 64, 72, CU_TENSOR_MAP_SWIZZLE_128B);
    fused_decode_kernel<<<NCTA, NTHREADS, SMEM_BYTES>>>(maps, (const __nv_bfloat16*)d_in[0], (__nv_bfloat16*)d_out, tau);
}
```

```cpp
#include <cuda_runtime.h>
#include <cuda.h>
#include <cuda_bf16.h>
#include <stdint.h>

namespace {

constexpr int D_MODEL = 576;
constexpr int NQ = 4096;
constexpr int FF = 4608;

constexpr int NCTA = 132;
constexpr int ATT_CTAS = 128;
constexpr int NTHREADS = 352;

constexpr int AW = 4;
constexpr int TP = 64;
constexpr int NT = 2048 / TP;
constexpr int SLOT = TP * 256;
constexpr int NSLOT = 13;
constexpr int CPB = 192 * 64;
constexpr int RPB = 8 * 1152;

#define DEPTH 8
#define TDEPTH 5
#define BW_EFF 0.945
#define T_OFF 600
#define XSLOW 10
#define POLL_AT 8
#define GLAG 16
#define QPOLL_AT 6
#define FIN_X 110
constexpr int KG = 4;

constexpr int IT_KV = 3, IT_W = IT_KV + 2 * NT, IT_END = IT_W + 14, XRING = 10;
static_assert(KG == AW && NT == 8 * KG, "one group of tiles per kv head");
__device__ constexpr int item_of_w(int j) { return IT_W + j; }

constexpr int OFF_RED = NSLOT * SLOT;
constexpr int OFF_XN = OFF_RED + 3 * 4 * 32 * 4;
constexpr int OFF_Q = OFF_XN + D_MODEL * 2;
constexpr int OFF_H = OFF_Q + 4096;
constexpr int OFF_O = OFF_H + 64;
constexpr int OFF_MO = OFF_O + 64;
constexpr int OFF_ML = OFF_MO + 2 * AW * 256 * 4;
constexpr int OFF_BAR = OFF_ML + 2 * AW * 16;
constexpr int OFF_ISSUED = OFF_BAR + (2 * NSLOT + 8) * 8;
constexpr int SMEM_BYTES = OFF_ISSUED + 16 + 1024;
static_assert(SMEM_BYTES <= 232448, "smem");

constexpr int NCOPY = 4;
constexpr int SPIN_LIMIT = 1 << 17;
constexpr int WAIT_LIMIT = 1 << 17;
constexpr float LOG2E = 1.4426950408889634f;

__device__ unsigned g_epoch;
__device__ __align__(128) unsigned long long g_q[NQ / 2];
__device__ __align__(128) uint32_t g_po[16][8][64][32];
__device__ __align__(128) uint32_t g_ml[16][64][32];
__device__ __align__(128) unsigned g_pub[2][32];
__device__ __align__(128) float4 g_acc[NCOPY][288];

__device__ __forceinline__ uint32_t smem_u32(const void* p) { return (uint32_t)__cvta_generic_to_shared(p); }
__device__ __forceinline__ void mbar_init(uint32_t bar, uint32_t cnt) {
    asm volatile("mbarrier.init.shared::cta.b64 [%0], %1;" ::"r"(bar), "r"(cnt) : "memory");
}
__device__ __forceinline__ void mbar_expect_tx(uint32_t bar, uint32_t bytes) {
    asm volatile("mbarrier.arrive.expect_tx.shared::cta.b64 _, [%0], %1;" ::"r"(bar), "r"(bytes) : "memory");
}
__device__ __forceinline__ void mbar_arrive(uint32_t bar) {
    asm volatile("mbarrier.arrive.shared::cta.b64 _, [%0];" ::"r"(bar) : "memory");
}
__device__ __forceinline__ void mbar_arrive4(uint32_t bar) {
    asm volatile("mbarrier.arrive.shared::cta.b64 _, [%0], 4;" ::"r"(bar) : "memory");
}
__device__ __forceinline__ void mbar_wait(uint32_t bar, uint32_t parity) {
    for (int it = 0; it < WAIT_LIMIT; it++) {
        uint32_t ok;
        asm volatile(
            "{\n.reg .pred p;\n"
            "mbarrier.try_wait.parity.shared::cta.b64 p, [%1], %2, %3;\n"
            "selp.u32 %0, 1, 0, p;\n}\n"
            : "=r"(ok) : "r"(bar), "r"(parity), "r"(1000) : "memory");
        if (ok) break;
    }
}
__device__ __forceinline__ void mbar_spin(uint32_t bar, uint32_t parity) {
    for (int it = 0; it < (1 << 22); it++) {
        uint32_t ok;
        asm volatile(
            "{\n.reg .pred p;\n"
            "mbarrier.test_wait.parity.shared::cta.b64 p, [%1], %2;\n"
            "selp.u32 %0, 1, 0, p;\n}\n"
            : "=r"(ok) : "r"(bar), "r"(parity) : "memory");
        if (ok) break;
    }
}
__device__ __forceinline__ unsigned long long gtime() {
    unsigned long long t;
    asm volatile("mov.u64 %0, %globaltimer;" : "=l"(t));
    return t;
}
__device__ __forceinline__ void tma2d(uint32_t dst, const CUtensorMap* map, int c0, int c1, uint32_t bar, uint64_t pol) {
    asm volatile(
        "cp.async.bulk.tensor.2d.shared::cluster.global.mbarrier::complete_tx::bytes.L2::cache_hint "
        "[%0], [%1, {%3, %4}], [%2], %5;"
        ::"r"(dst), "l"(map), "r"(bar), "r"(c0), "r"(c1), "l"(pol) : "memory");
}
__device__ __forceinline__ unsigned long long pack_pkt(float v, unsigned tag) {
    return (unsigned long long)__float_as_uint(v) | ((unsigned long long)tag << 32);
}
__device__ __forceinline__ void st_pkt(unsigned long long* p, unsigned long long v) {
    asm volatile("st.relaxed.gpu.global.b64 [%0], %1;" ::"l"(p), "l"(v) : "memory");
}
__device__ __forceinline__ void ld_pkt2(const unsigned long long* p, unsigned long long& a, unsigned long long& b) {
    asm volatile("ld.relaxed.gpu.global.v2.b64 {%0, %1}, [%2];" : "=l"(a), "=l"(b) : "l"(p) : "memory");
}
__device__ __forceinline__ void st_word(uint32_t* p, float v, unsigned tag) {
    asm volatile("st.relaxed.gpu.global.u32 [%0], %1;" ::"l"(p), "r"((__float_as_uint(v) & ~15u) | (tag & 15u)) : "memory");
}
__device__ __forceinline__ uint4 ld_word4(const uint32_t* p) {
    uint4 v;
    asm volatile("ld.relaxed.gpu.global.v4.u32 {%0,%1,%2,%3}, [%4];" : "=r"(v.x), "=r"(v.y), "=r"(v.z), "=r"(v.w) : "l"(p) : "memory");
    return v;
}
__device__ __forceinline__ bool fresh4(const uint4& v, unsigned tag) {
    return (((v.x ^ tag) | (v.y ^ tag) | (v.z ^ tag) | (v.w ^ tag)) & 15u) == 0;
}
__device__ __forceinline__ float word_val(uint32_t v) { return __uint_as_float(v & ~15u); }
__device__ __forceinline__ float pkt_val(unsigned long long v) { return __uint_as_float((unsigned)v); }
__device__ __forceinline__ unsigned pkt_tag(unsigned long long v) { return (unsigned)(v >> 32); }

__device__ __forceinline__ float bf16r(float v) { return __bfloat162float(__float2bfloat16_rn(v)); }
__device__ __forceinline__ float bf_lo(uint32_t v) { return __uint_as_float(v << 16); }
__device__ __forceinline__ float bf_hi(uint32_t v) { return __uint_as_float(v & 0xffff0000u); }
__device__ __forceinline__ uint32_t pack_bf16(float lo, float hi) {
    uint32_t r;
    asm("cvt.rn.bf16x2.f32 %0, %1, %2;" : "=r"(r) : "f"(hi), "f"(lo));
    return r;
}
__device__ __forceinline__ float ex2(float x) {
    float r;
    asm("ex2.approx.ftz.f32 %0, %1;" : "=f"(r) : "f"(x));
    return r;
}
__device__ __forceinline__ void ldsm4(uint32_t addr, uint32_t (&r)[4]) {
    asm volatile("ldmatrix.sync.aligned.m8n8.x4.shared.b16 {%0,%1,%2,%3}, [%4];"
                 : "=r"(r[0]), "=r"(r[1]), "=r"(r[2]), "=r"(r[3]) : "r"(addr) : "memory");
}
__device__ __forceinline__ void ldsm4t(uint32_t addr, uint32_t (&r)[4]) {
    asm volatile("ldmatrix.sync.aligned.m8n8.x4.trans.shared.b16 {%0,%1,%2,%3}, [%4];"
                 : "=r"(r[0]), "=r"(r[1]), "=r"(r[2]), "=r"(r[3]) : "r"(addr) : "memory");
}
__device__ __forceinline__ void mma16816(float (&c)[4], const uint32_t (&a)[4], uint32_t b0, uint32_t b1) {
    asm volatile(
        "mma.sync.aligned.m16n8k16.row.col.f32.bf16.bf16.f32 {%0,%1,%2,%3}, {%4,%5,%6,%7}, {%8,%9}, {%0,%1,%2,%3};"
        : "+f"(c[0]), "+f"(c[1]), "+f"(c[2]), "+f"(c[3])
        : "r"(a[0]), "r"(a[1]), "r"(a[2]), "r"(a[3]), "r"(b0), "r"(b1));
}
__device__ __forceinline__ uint32_t movmat(uint32_t a) {
    uint32_t d;
    asm volatile("movmatrix.sync.aligned.m8n8.trans.b16 %0, %1;" : "=r"(d) : "r"(a));
    return d;
}
__device__ __forceinline__ void named_bar(int id, int n) {
    asm volatile("bar.sync %0, %1;" ::"r"(id), "r"(n) : "memory");
}
__device__ __forceinline__ void named_arrive(int id, int n) {
    asm volatile("bar.arrive %0, %1;" ::"r"(id), "r"(n) : "memory");
}

struct Maps {
    CUtensorMap k, v, wq, wg, wu, wd, wo;
};

__global__ void __launch_bounds__(NTHREADS, 1)
fused_decode_kernel(const __grid_constant__ Maps maps, const __nv_bfloat16* __restrict__ x,
                    __nv_bfloat16* __restrict__ out, const unsigned tau) {
    extern __shared__ unsigned char smem_raw[];
    const uint32_t sbase = (smem_u32(smem_raw) + 1023u) & ~1023u;
    const uint32_t full0 = sbase + OFF_BAR, empty0 = full0 + 8 * NSLOT, qbar0 = empty0 + 8 * NSLOT;
    const int tid = threadIdx.x, cta = blockIdx.x;
    const bool att = cta < ATT_CTAS;
    unsigned char* smem = smem_raw + (sbase - smem_u32(smem_raw));
    volatile int* issued_s = reinterpret_cast<volatile int*>(smem + OFF_ISSUED);
    const int ring = att ? NSLOT : XRING;
    if (tid >= 288 && tid < 320) {
        if (tid != 288) asm volatile("exit;");
        const unsigned t0 = (unsigned)gtime();
        uint64_t pol, polw;
#pragma unroll
        for (int b = 0; b < 3; b++) mbar_init(full0 + 8 * b, 1);
        asm volatile("fence.mbarrier_init.release.cluster;" ::: "memory");
        asm volatile("createpolicy.fractional.L2::evict_normal.b64 %0, 1.0;" : "=l"(polw));
        int unit = att ? cta : ATT_CTAS + (cta - ATT_CTAS) * 4;
#pragma unroll
        for (int b = 0; b < 3; b++) {
            mbar_expect_tx(full0 + 8 * b, CPB);
            tma2d(sbase + b * SLOT, att ? &maps.wq : (b & 1) ? &maps.wu : &maps.wg, unit * 32, (att ? b : b >> 1) * 192,
                  full0 + 8 * b, polw);
        }
#pragma unroll 1
        for (int i = 0; i < 7; i++) asm volatile("prefetch.tensormap [%0];" ::"l"(&maps.k + i) : "memory");
#pragma unroll 1
        for (int i = 3; i < 2 * NSLOT + 8; i++) mbar_init(full0 + 8 * i, i >= NSLOT && i < 2 * NSLOT ? 4 : 1);
        *issued_s = 3;
        asm volatile("fence.mbarrier_init.release.cluster;" ::: "memory");
        named_arrive(6, NTHREADS);
        asm volatile("createpolicy.fractional.L2::evict_first.b64 %0, 1.0;" : "=l"(pol));
        const int nitems = att ? IT_END : 4 * XRING;
        int slot = 3, ph = 0, lslot = 0, lph = 0, landed = 0, depth = DEPTH;
        unsigned due = T_OFF << 4;
        int n = att ? 0 : NT, half = 0, j = att ? 0 : 3;
#pragma unroll 1
        for (int i = 3; i < nitems; i++) {
            if (!att && j == XRING) { j = 0; unit++; }
            const uint32_t bar = full0 + 8 * slot, dst = sbase + slot * SLOT;
            if (i >= ring) mbar_wait(empty0 + 8 * slot, ph ^ 1);
            while (landed <= i - depth) {
                mbar_wait(full0 + 8 * lslot, lph);
                landed++;
                if (++lslot == ring) { lslot = 0; lph ^= 1; }
            }
            if (n < NT || !att)
                for (int it = 0; (int)((unsigned)gtime() - t0 - (due >> 4)) < 0 && it < (1 << 22); it++) {}
            uint32_t bytes;
            if (n < NT) {
                const CUtensorMap* m = half >= KG ? &maps.v : &maps.k;
                const int row = (cta >> 6) * (8 * 16384) + ((n + (half >= KG ? half - KG : half)) * 64 + (cta & 63)) * TP;
                bytes = SLOT;
                mbar_expect_tx(bar, SLOT);
                tma2d(dst, m, 0, row, bar, pol);
                tma2d(dst + SLOT / 2, m, 64, row, bar, pol);
                if (++half == 2 * KG) { half = 0; n += KG; }
            } else if (j < 6) {
                const CUtensorMap* m = (j & 1) ? &maps.wu : &maps.wg;
                bytes = CPB;
                mbar_expect_tx(bar, CPB);
                tma2d(dst, m, unit * 32, (j >> 1) * 192, bar, polw);
                j++;
            } else {
                bytes = RPB;
                mbar_expect_tx(bar, RPB);
                tma2d(dst, j < 10 ? &maps.wd : &maps.wo, 0, unit * 288 + ((j - 6) & 3) * 72, bar, pol);
                j++;
            }
            due += (bytes >> 10) * (att ? tau : tau * XSLOW / 4);
            *issued_s = i + 1;
            if (n == NT) depth = TDEPTH;
            if (++slot == ring) { slot = 0; ph ^= 1; }
        }
        asm volatile("exit;");
    }
    const int lane = tid & 31;
    const int warp = __shfl_sync(0xffffffffu, tid >> 5, 0);
    float* red_s = reinterpret_cast<float*>(smem + OFF_RED);
    uint32_t* xn32 = reinterpret_cast<uint32_t*>(smem + OFF_XN);
    const int g = lane >> 2, t = lane & 3;
    const int lr = lane & 7, mi = lane >> 3;

    auto wait_item = [&](int i, int sleep_ns) {
        for (int it = 0; *issued_s <= i && it < SPIN_LIMIT; it++) __nanosleep(sleep_ns);
        const int q = att ? i / NSLOT : i / XRING, sl = i - q * ring;
        mbar_wait(full0 + 8 * sl, q & 1);
        __syncwarp();
        return sl;
    };

    unsigned tag = 0;
    asm volatile("ld.relaxed.gpu.global.u32 %0, [%1];" : "=r"(tag) : "l"(&g_epoch) : "memory");
    if (warp < 9) {
        uint32_t xs[9];
#pragma unroll
        for (int i = 0; i < 9; i++) xs[i] = __ldg(reinterpret_cast<const uint32_t*>(x) + lane + 32 * i);
        float s = 0.f;
#pragma unroll
        for (int i = 0; i < 9; i++) s += bf_lo(xs[i]) + bf_hi(xs[i]);
#pragma unroll
        for (int o = 16; o; o >>= 1) s += __shfl_xor_sync(0xffffffffu, s, o);
        const float mean = s * (1.f / D_MODEL);
        float vs = 0.f;
#pragma unroll
        for (int i = 0; i < 9; i++) {
            float a = bf_lo(xs[i]) - mean, b = bf_hi(xs[i]) - mean;
            vs += a * a + b * b;
        }
#pragma unroll
        for (int o = 16; o; o >>= 1) vs += __shfl_xor_sync(0xffffffffu, vs, o);
        const float mb = bf16r(mean);
        const float den = bf16r(sqrtf(bf16r(bf16r(vs * (1.f / D_MODEL)) + 1e-5f)));
        uint32_t mine = xs[0];
#pragma unroll
        for (int i = 1; i < 9; i++) mine = (warp == i) ? xs[i] : mine;
        xn32[tid] = pack_bf16(bf16r(bf_lo(mine) - mb) / den, bf16r(bf_hi(mine) - mb) / den);
    }
    named_bar(6, NTHREADS);
    tag += 1;

    if (warp == 10) {
        if (!att) return;
        const int H = cta >> 3, eo = H & 7;
        wait_item(QPOLL_AT, 100);
#pragma unroll 1
        for (int e = 0; e < 9; e++) {
            if (e < 8) {
                if (e > 1)
                    for (int it = 0; *issued_s < IT_KV + 2 * KG * (e - 1) && it < SPIN_LIMIT; it++) __nanosleep(200);
                const unsigned long long* src = &g_q[(cta >> 6) * 1024 + e * 128 + lane * 2];
                unsigned long long a[2], b[2];
                for (int it = 0; it < SPIN_LIMIT; it++) {
                    ld_pkt2(src, a[0], b[0]);
                    ld_pkt2(src + 64, a[1], b[1]);
                    if (pkt_tag(a[0]) == tag && pkt_tag(b[0]) == tag && pkt_tag(a[1]) == tag && pkt_tag(b[1]) == tag) break;
                    __nanosleep(200);
                }
                uint2* qs = reinterpret_cast<uint2*>(smem + OFF_Q) + e * 64 + lane;
                qs[0] = make_uint2((unsigned)a[0], (unsigned)b[0]);
                qs[32] = make_uint2((unsigned)a[1], (unsigned)b[1]);
                __syncwarp();
                if (lane == 0) mbar_arrive(qbar0 + 8 * e);
            }
            if (e != min(eo + 4, 8)) continue;
            const int when = min(IT_KV + 2 * KG * (eo + 1) + GLAG, IT_W + POLL_AT);
            for (int it = 0; *issued_s < when && it < SPIN_LIMIT; it++) __nanosleep(100);
            if (eo == 7) {
                for (int it = 0; it < SPIN_LIMIT; it++) {
                    unsigned c;
                    asm volatile("ld.relaxed.gpu.global.u32 %0, [%1];" : "=r"(c) : "l"(&g_pub[cta >> 6][0]) : "memory");
                    if (c >= 128u) break;
                    __nanosleep(200);
                }
                __nanosleep(500);
            }
            const uint32_t* src = &g_po[H][cta & 7][0][lane * 4];
            uint4 a[18];
            unsigned pend = 0x3ffffu;
            for (int it = 0; pend && it < SPIN_LIMIT; it++) {
                if (it) __nanosleep(200);
#pragma unroll
                for (int j = 0; j < 18; j++)
                    if (pend >> j & 1) a[j] = ld_word4(j < 16 ? src + j * 128 : &g_ml[H][lane + (j - 16) * 32][0]);
#pragma unroll
                for (int j = 0; j < 18; j++)
                    if (fresh4(a[j], tag)) pend &= ~(1u << j);
            }
            __syncwarp();
            const bool hs = cta & 4;
            const float m0 = word_val(hs ? a[16].z : a[16].x), m1 = word_val(hs ? a[17].z : a[17].x);
            float M = fmaxf(m0, m1);
#pragma unroll
            for (int off = 16; off; off >>= 1) M = fmaxf(M, __shfl_xor_sync(0xffffffffu, M, off));
            const float w0 = ex2((m0 - M) * LOG2E), w1 = ex2((m1 - M) * LOG2E);
            float L = w0 * word_val(hs ? a[16].w : a[16].y) + w1 * word_val(hs ? a[17].w : a[17].y);
#pragma unroll
            for (int off = 16; off; off >>= 1) L += __shfl_xor_sync(0xffffffffu, L, off);
            float acc[4] = {};
#pragma unroll
            for (int j = 0; j < 16; j++) {
                const float w = __shfl_sync(0xffffffffu, j < 8 ? w0 : w1, (4 * j + (lane >> 3)) & 31);
                acc[0] = fmaf(word_val(a[j].x), w, acc[0]);
                acc[1] = fmaf(word_val(a[j].y), w, acc[1]);
                acc[2] = fmaf(word_val(a[j].z), w, acc[2]);
                acc[3] = fmaf(word_val(a[j].w), w, acc[3]);
            }
#pragma unroll
            for (int i = 0; i < 4; i++) {
                acc[i] += __shfl_xor_sync(0xffffffffu, acc[i], 8);
                acc[i] += __shfl_xor_sync(0xffffffffu, acc[i], 16);
            }
            if (lane < 8)
                reinterpret_cast<uint2*>(smem + OFF_O)[lane] =
                    make_uint2(pack_bf16(acc[0] / L, acc[1] / L), pack_bf16(acc[2] / L, acc[3] / L));
        }
        __syncwarp();
        named_arrive(1, 320);
        return;
    }

    float res[4][4] = {};
    float4* accp = &g_acc[cta % NCOPY][warp * 32 + t * 8 + g];
    asm volatile("" : "+l"(accp));
#pragma unroll 1
    for (int u = 0;;) {
        if (warp >= 4 && warp < 8) {
            const int fw = warp - 4;
            const uint32_t coff = ((fw * 48 + (mi >> 1) * 8 + lr) << 6) + (((mi & 1) ^ ((lr >> 1) & 3)) << 4);
            float s0 = 0.f, s1 = 0.f;
#pragma unroll 1
            for (int p = att ? -3 : 0; p < 6; p++) {
                const int pc = p < 0 ? p + 3 : p >> 1;
                uint32_t b[3][2];
#pragma unroll
                for (int ks = 0; ks < 3; ks++) {
                    b[ks][0] = xn32[pc * 96 + fw * 24 + ks * 8 + t];
                    b[ks][1] = xn32[pc * 96 + fw * 24 + ks * 8 + 4 + t];
                }
                const int sl = wait_item(p < 0 ? pc : att ? item_of_w(p) : XRING * u + p, 200);
                float acc[2][4] = {};
#pragma unroll
                for (int ks = 0; ks < 3; ks++)
#pragma unroll
                    for (int mt = 0; mt < 2; mt++) {
                        uint32_t a[4];
                        ldsm4t(sbase + sl * SLOT + ((coff + ks * 1024) ^ (mt << 5)), a);
                        mma16816(acc[mt], a, b[ks][0], b[ks][1]);
                    }
                if (lane == 0) mbar_arrive(empty0 + 8 * sl);
                const float val = (t & 2) ? ((t & 1) ? acc[1][2] : acc[1][0]) : ((t & 1) ? acc[0][2] : acc[0][0]);
                if (p >= 0 && (p & 1)) s1 += val; else s0 += val;
                if (p == -1 || p == 5) {
                    const int o = p < 0 ? 0 : 128;
                    red_s[o + fw * 32 + 8 * t + g] = s0;
                    red_s[256 + fw * 32 + 8 * t + g] = s1;
                    s0 = 0.f;
                    named_bar(3, 128);
                    if (p < 0 && warp == 4) {
                        const float qv = red_s[lane] + red_s[32 + lane] + red_s[64 + lane] + red_s[96 + lane];
                        const uint32_t q2 = pack_bf16(qv, __shfl_down_sync(0xffffffffu, qv, 1));
                        if (!(lane & 1)) st_pkt(&g_q[cta * 16 + (lane >> 1)], pack_pkt(__uint_as_float(q2), tag));
                    }
                }
            }
        } else if (att && warp < AW) {
            const uint32_t koff = sbase + ((mi & 1) * 8 + lr) * 128 + (((mi >> 1) ^ lr) << 4);
            const uint32_t voff = sbase + ((mi >> 1) * 8 + lr) * 128 + (((mi & 1) ^ lr) << 4);
            constexpr float SCALE = 0.08838834764831845f;
#pragma unroll 1
            for (int e = 0; e < 8; e++) {
                mbar_wait(qbar0 + 8 * e, 0);
                uint32_t qf[8][2];
                const uint32_t* q32 = reinterpret_cast<const uint32_t*>(smem + OFF_Q) + e * 128 + (g & 1) * 64 + t;
#pragma unroll
                for (int ks = 0; ks < 8; ks++) {
                    qf[ks][0] = q32[ks * 8];
                    qf[ks][1] = q32[ks * 8 + 4];
                }
                const int ik = IT_KV + 2 * KG * e + warp;
                const int ks_ = wait_item(ik, 50);
                const uint32_t kaddr = koff + ks_ * SLOT;
                float sc[4][4] = {};
#pragma unroll
                for (int ks = 0; ks < 8; ks++) {
#pragma unroll
                    for (int i = 0; i < 4; i++) {
                        uint32_t a[4];
                        ldsm4((kaddr ^ ((ks & 3) << 5)) + (ks >> 2) * (SLOT / 2) + i * 2048, a);
                        mma16816(sc[i], a, qf[ks][0], qf[ks][1]);
                    }
                }
                if (lane == 0) mbar_arrive4(empty0 + 8 * ks_);
                float v[4];
#pragma unroll
                for (int j = 0; j < 4; j++) {
                    float a = (t & 1) ? sc[1][j] : sc[0][j];
                    float b = (t & 1) ? sc[3][j] : sc[2][j];
                    v[j] = bf16r(bf16r((t & 2) ? b : a) * SCALE);
                }
                float m0 = fmaxf(v[0], v[2]), m1 = fmaxf(v[1], v[3]);
#pragma unroll
                for (int off = 1; off <= 16; off <<= 1) {
                    m0 = fmaxf(m0, __shfl_xor_sync(0xffffffffu, m0, off));
                    m1 = fmaxf(m1, __shfl_xor_sync(0xffffffffu, m1, off));
                }
                const float p0 = ex2((v[0] - m0) * LOG2E), p1 = ex2((v[1] - m1) * LOG2E);
                const float p2 = ex2((v[2] - m0) * LOG2E), p3 = ex2((v[3] - m1) * LOG2E);
                const uint32_t blo = movmat(pack_bf16(p0, p1));
                const uint32_t bhi = movmat(pack_bf16(p2, p3));
                float l0 = p0 + p2, l1 = p1 + p3;
#pragma unroll
                for (int off = 1; off <= 16; off <<= 1) {
                    l0 += __shfl_xor_sync(0xffffffffu, l0, off);
                    l1 += __shfl_xor_sync(0xffffffffu, l1, off);
                }
                float* mo = reinterpret_cast<float*>(smem + OFF_MO) + (e & 1) * (AW * 256);
                float* ml = reinterpret_cast<float*>(smem + OFF_ML) + (e & 1) * (AW * 4);
                if (lane == 0) *reinterpret_cast<float4*>(ml + warp * 4) = make_float4(m0, l0, m1, l1);
                const int vs_ = wait_item(ik + KG, 50);
                const uint32_t vaddr = voff + vs_ * SLOT;
                float o[8][4] = {};
#pragma unroll
                for (int i = 0; i < 4; i++) {
                    const uint32_t b0 = ((g >> 1) == i) ? blo : 0u, b1 = ((g >> 1) == i) ? bhi : 0u;
#pragma unroll
                    for (int md = 0; md < 8; md++) {
                        uint32_t a[4];
                        ldsm4t((vaddr ^ ((md & 3) << 5)) + (md >> 2) * (SLOT / 2) + i * 2048, a);
                        mma16816(o[md], a, b0, b1);
                    }
                }
                if (lane == 0) mbar_arrive4(empty0 + 8 * vs_);
#pragma unroll
                for (int md = 0; md < 8; md++) {
                    const bool u1 = t & 1, u2 = t & 2;
                    float k0 = u2 ? o[md][2] : o[md][0], k1 = u2 ? o[md][3] : o[md][1];
                    k0 += __shfl_xor_sync(0xffffffffu, u2 ? o[md][0] : o[md][2], 2);
                    k1 += __shfl_xor_sync(0xffffffffu, u2 ? o[md][1] : o[md][3], 2);
                    float k = u1 ? k1 : k0;
                    k += __shfl_xor_sync(0xffffffffu, u1 ? k0 : k1, 1);
                    mo[warp * 256 + (t & 1) * 128 + md * 16 + g + (t >> 1) * 8] = k;
                }
                named_bar(7, 32 * AW);
                const int H = (cta >> 6) * 8 + e;
                float Mh[2], Lh[2];
#pragma unroll
                for (int hs = 0; hs < 2; hs++) {
                    float M = -INFINITY, acc = 0.f, L = 0.f;
#pragma unroll
                    for (int w = 0; w < AW; w++) M = fmaxf(M, ml[w * 4 + hs * 2]);
#pragma unroll
                    for (int w = 0; w < AW; w++) {
                        const float f = ex2((ml[w * 4 + hs * 2] - M) * LOG2E);
                        acc = fmaf(mo[w * 256 + hs * 128 + warp * 32 + lane], f, acc);
                        L = fmaf(ml[w * 4 + hs * 2 + 1], f, L);
                    }
                    st_word(&g_po[H][hs * 4 + warp][cta & 63][lane], acc, tag);
                    Mh[hs] = M;
                    Lh[hs] = L;
                }
                if (warp == 0)
                    st_word(&g_ml[H][cta & 63][lane], (lane & 2) ? ((lane & 1) ? Lh[1] : Mh[1]) : ((lane & 1) ? Lh[0] : Mh[0]), tag);
                if (e >= 6 && tid == 0)
                    asm volatile("red.relaxed.gpu.global.add.u32 [%0], 1;" ::"l"(&g_pub[cta >> 6][0]) : "memory");
            }
        }
        if (warp == 4) {
            const float gv = bf16r(red_s[128 + lane] + red_s[160 + lane] + red_s[192 + lane] + red_s[224 + lane]);
            const float uv = bf16r(red_s[256 + lane] + red_s[288 + lane] + red_s[320 + lane] + red_s[352 + lane]);
            const float sg = bf16r(gv / (1.f + __expf(-gv)));
            reinterpret_cast<__nv_bfloat16*>(smem + OFF_H)[lane] = __float2bfloat16_rn(sg * uv);
        }
        const uint32_t roff = ((lr * 9 + warp) << 7) + (((mi & 1) ^ ((lr + warp) & 7)) << 4);
#pragma unroll 1
        for (int k = 0; k < (att ? 4 : 2); k++) {
            if (k == 0) named_bar(2, 288);
            if (k == 2) named_bar(1, 320);
            const uint32_t* v32 = reinterpret_cast<const uint32_t*>(smem + OFF_H) + 8 * k;
            const uint32_t b0 = v32[t], b1 = v32[4 + t];
            const int item = (att ? item_of_w(6) : XRING * u + 6) + 2 * k;
            const int q0 = att ? item / NSLOT : u, q1 = att ? (item + 1) / NSLOT : u;
            const int s0 = item - q0 * ring, s1 = item + 1 - q1 * ring;
            const uint32_t base = sbase + ((mi >> 1) ? s1 : s0) * SLOT;
            for (int it = 0; *issued_s <= item + 1 && it < SPIN_LIMIT; it++) __nanosleep(20);
            mbar_spin(full0 + 8 * s0, q0 & 1);
            mbar_spin(full0 + 8 * s1, q1 & 1);
            __syncwarp();
#pragma unroll
            for (int mt = 0; mt < 4; mt++) {
                uint32_t a[4];
                ldsm4t(base + (roff ^ (mt << 5)), a);
                mma16816(res[mt], a, b0, b1);
            }
        }
        if (!att) {
            named_bar(2, 288);
            if (tid < 4) mbar_arrive4(empty0 + 8 * (6 + tid));
            if (++u < 4) continue;
        }
        break;
    }
    {
        const float r0 = (t & 2) ? ((t & 1) ? res[3][0] : res[2][0]) : ((t & 1) ? res[1][0] : res[0][0]);
        const float r1 = (t & 2) ? ((t & 1) ? res[3][2] : res[2][2]) : ((t & 1) ? res[1][2] : res[0][2]);
        asm volatile("red.relaxed.gpu.global.add.v4.f32 [%0], {%1, %2, %3, %4};"
                     ::"l"(accp), "f"(r0), "f"(r1), "f"(1.0f), "f"(0.0f) : "memory");
    }

    if (!att) {
        const int slot = (cta - ATT_CTAS) * 72 + (tid >> 2), copy = tid & 3;
        const int col = (slot >> 3) * 16 + (slot & 7) + (copy & 1) * 8;
        float4* src = &g_acc[copy][slot];
        const float xv = __bfloat162float(x[col]);
        __nv_bfloat16* dst = out + col;
        asm volatile("" : "+l"(dst));
        unsigned long long a = 0, b = 0;
        if (warp == 0) {
#pragma unroll 1
            for (int it = 0; it < SPIN_LIMIT; it++) {
                float cnt = 0.f;
                if (lane < 4) {
                    ld_pkt2(reinterpret_cast<const unsigned long long*>(src), a, b);
                    cnt = pkt_val(b);
                }
                cnt += __shfl_xor_sync(0xffffffffu, cnt, 1);
                cnt += __shfl_xor_sync(0xffffffffu, cnt, 2);
                cnt = __shfl_sync(0xffffffffu, cnt, 0);
                if (cnt >= (float)(NCTA - FIN_X)) break;
                __nanosleep(cnt > 8.f ? 100 : 300);
            }
        }
        named_bar(2, 288);
#pragma unroll 1
        for (int it = 0; it < SPIN_LIMIT; it++) {
            ld_pkt2(reinterpret_cast<const unsigned long long*>(src), a, b);
            if (pkt_val(b) == (float)(NCTA / NCOPY)) break;
        }
        __syncwarp();
        const float s0 = pkt_val(a), s1 = __uint_as_float(pkt_tag(a));
        float k = (copy & 1) ? s1 : s0;
        k += __shfl_xor_sync(0xffffffffu, (copy & 1) ? s0 : s1, 1);
        k += __shfl_xor_sync(0xffffffffu, k, 2);
        if (copy < 2) *dst = __float2bfloat16_rn(xv + k);
        *src = make_float4(0.f, 0.f, 0.f, 0.f);
        if (cta == ATT_CTAS && tid == 0) { g_epoch = tag; g_pub[0][0] = 0; g_pub[1][0] = 0; }
    }
}

typedef CUresult (*EncodeFn)(CUtensorMap*, CUtensorMapDataType, cuuint32_t, void*, const cuuint64_t*, const cuuint64_t*,
                             const cuuint32_t*, const cuuint32_t*, CUtensorMapInterleave, CUtensorMapSwizzle,
                             CUtensorMapL2promotion, CUtensorMapFloatOOBfill);

void make_map(EncodeFn enc, CUtensorMap* m, void* base, uint64_t cols, uint64_t rows, uint32_t bc, uint32_t br,
              CUtensorMapSwizzle sw) {
    cuuint64_t gd[2] = {cols, rows};
    cuuint64_t gs[1] = {cols * 2};
    cuuint32_t bx[2] = {bc, br};
    cuuint32_t es[2] = {1, 1};
    enc(m, CU_TENSOR_MAP_DATA_TYPE_BFLOAT16, 2, base, gd, gs, bx, es, CU_TENSOR_MAP_INTERLEAVE_NONE, sw,
        CU_TENSOR_MAP_L2_PROMOTION_L2_256B, CU_TENSOR_MAP_FLOAT_OOB_FILL_NONE);
}

}

extern "C" void kernel_launch(void* const* d_in, const int* in_sizes, int n_in, void* d_out, int out_size) {
    (void)in_sizes; (void)n_in; (void)out_size;
    static EncodeFn enc = nullptr;
    static unsigned tau = 662;
    if (!enc) {
        int dev = 0, khz = 0, bits = 0;
        cudaGetDevice(&dev);
        if (cudaDeviceGetAttribute(&khz, cudaDevAttrMemoryClockRate, dev) == cudaSuccess &&
            cudaDeviceGetAttribute(&bits, cudaDevAttrGlobalMemoryBusWidth, dev) == cudaSuccess && khz > 0 && bits > 0)
            tau = (unsigned)(ATT_CTAS * 16384.0 / (BW_EFF * 2.0 * khz * 1e-6 * (bits / 8)) + 0.5);
        void* fn = nullptr;
        cudaDriverEntryPointQueryResult qr;
        cudaGetDriverEntryPoint("cuTensorMapEncodeTiled", &fn, cudaEnableDefault, &qr);
        enc = (EncodeFn)fn;
        cudaFuncSetAttribute(fused_decode_kernel, cudaFuncAttributeMaxDynamicSharedMemorySize, SMEM_BYTES);
    }
    Maps maps;
    make_map(enc, &maps.k, d_in[1], 128, 16 * 16384, 64, TP, CU_TENSOR_MAP_SWIZZLE_128B);
    make_map(enc, &maps.v, d_in[2], 128, 16 * 16384, 64, TP, CU_TENSOR_MAP_SWIZZLE_128B);
    make_map(enc, &maps.wq, d_in[3], NQ, D_MODEL, 32, 192, CU_TENSOR_MAP_SWIZZLE_64B);
    make_map(enc, &maps.wg, d_in[6], FF, D_MODEL, 32, 192, CU_TENSOR_MAP_SWIZZLE_64B);
    make_map(enc, &maps.wu, d_in[7], FF, D_MODEL, 32, 192, CU_TENSOR_MAP_SWIZZLE_64B);
    make_map(enc, &maps.wd, d_in[8], 64, FF * 9, 64, 72, CU_TENSOR_MAP_SWIZZLE_128B);
    make_map(enc, &maps.wo, d_in[4], 64, NQ * 9, 64, 72, CU_TENSOR_MAP_SWIZZLE_128B);
    fused_decode_kernel<<<NCTA, NTHREADS, SMEM_BYTES>>>(maps, (const __nv_bfloat16*)d_in[0], (__nv_bfloat16*)d_out, tau);
}
```
